```python
import torch

def _softmax(x, axis=-1):
    return torch.softmax(x, dim=axis)

def _gelu(x):
    return torch.nn.functional.gelu(x, approximate='tanh')

def _silu(x):
    return torch.nn.functional.silu(x)

def _sigmoid(x):
    return torch.sigmoid(x)

def _layernorm(x, axis=-1, eps=1e-05):
    m = x.mean(dim=axis, keepdim=True)
    v = x.var(dim=axis, keepdim=True, unbiased=False)
    return (x - m) / torch.sqrt(v + eps)

def _scatter_add(tgt, idx, src, axis=0):
    return tgt.clone().index_add_(axis, idx, src)

def _segment_sum(src, seg, n):
    out = torch.zeros((n,) + src.shape[1:], dtype=src.dtype)
    return out.index_add_(0, seg, src)

def _pad(x, pw):
    flat = tuple((v for pair in reversed(pw) for v in pair))
    return torch.nn.functional.pad(x, flat)
kernel_name = 'adaLN_cond__ssm_conv_h3__dense_activation_silu__prompt'

def setup_inputs():

    _w = lambda a: (lambda t: t.to(torch.bfloat16) if t.is_floating_point() else t)(torch.as_tensor(a))

    def _A_setup():
        B, S, D = (1, 2048, 512)
        ks = 4
        return {'q': _w((lambda *s: torch.randn(*s, dtype=torch.bfloat16) * 0.05)(B, S, D)), 'k': _w((lambda *s: torch.randn(*s, dtype=torch.bfloat16) * 0.8)(B, S, D)), 'v': _w((lambda *s: torch.randn(*s, dtype=torch.bfloat16) * 0.8)(B, S, D)), 'shift_k': _w((lambda *s: torch.randn(*s, dtype=torch.bfloat16) * 0.8)(D, ks) * 0.5), 'ssm_k': _w((lambda *s: torch.randn(*s, dtype=torch.bfloat16) * 0.8)(D, S) * (1.0 / S ** 0.5)), 'ssm_D': _w((lambda *s: torch.randn(*s, dtype=torch.bfloat16) * 0.8)(D))}
    _A_in = _A_setup()

    def _B_setup():
        B, S, D, F = (1, 2048, 512, 1792)
        return {'x': _w((lambda *s: torch.randn(*s, dtype=torch.bfloat16) * 0.05)(B, S, D)), 'w1': _w((lambda *s: torch.randn(*s, dtype=torch.bfloat16) * 3.2)(D, F) * D ** (-0.5)), 'w2': _w((lambda *s: torch.randn(*s, dtype=torch.bfloat16) * 0.8)(F, D) * F ** (-0.5))}
    _B_in = _B_setup()
    return {'A_q': _A_in['q'], 'A_k': _A_in['k'], 'A_v': _A_in['v'], 'A_shift_k': _A_in['shift_k'], 'A_ssm_k': _A_in['ssm_k'], 'A_ssm_D': _A_in['ssm_D'], 'B_x': _B_in['x'], 'B_w1': _B_in['w1'], 'B_w2': _B_in['w2'], 'c': _w((lambda *s: torch.randn(*s, dtype=torch.bfloat16) * 0.2)(1, 512) * 8.0), 'w_mod': _w((lambda *s: torch.randn(*s, dtype=torch.bfloat16) * 0.2)(512, 6 * 512) * 512 ** (-0.5) * 8.0)}

def reference(A_q, A_k, A_v, A_shift_k, A_ssm_k, A_ssm_D, B_x, B_w1, B_w2, c, w_mod):

    def _A_ref(q, k, v, shift_k, ssm_k, ssm_D):
        B, S, D = q.shape
        ks = shift_k.shape[-1]
        k_pad = _pad(k, ((0, 0), (ks - 1, 0), (0, 0)))
        k_shift = torch.zeros_like(k)
        for t in range(ks):
            k_shift = k_shift + k_pad[:, t:t + S, :] * shift_k[:, ks - 1 - t][None, None, :]
        kv = k_shift * v
        L = 2 * S
        kv_pad = _pad(kv, ((0, 0), (0, S), (0, 0)))
        kf_pad = _pad(ssm_k, ((0, 0), (0, S)))
        kv_f = (lambda x, axes=(-2, -1): torch.fft.rfft2(x.float(), dim=axes))(kv_pad[:, None, :, :], axes=(1, 2))
        kf_f = (lambda x, axes=(-2, -1): torch.fft.rfft2(x.float(), dim=axes))(kf_pad[:, None, :], axes=(1, 2))
        kf_f = (lambda x, *d: x.permute(*d))(kf_f, 1, 2, 0)
        y_f = kv_f * kf_f[None, :, :, :]
        y = (lambda x, s, axes=(-2, -1): torch.fft.irfft2(x, s=s, dim=axes).to(torch.bfloat16))(y_f, (1, L), axes=(1, 2))[:, 0, :S, :]
        y = y + kv * ssm_D[None, None, :]
        return q * y

    def _B_ref(x, w1, w2):
        h = torch.einsum('bsd,df->bsf', x, w1)
        h = _silu(h)
        out = torch.einsum('bsf,fd->bsd', h, w2)
        return out
    x = A_q
    mod = (_silu(c) @ w_mod).reshape(c.shape[0], 6, 1, -1)
    sa, ca, ga, sb, cb, gb = (mod[:, 0].clone(), mod[:, 1].clone(), mod[:, 2].clone(), mod[:, 3].clone(), mod[:, 4].clone(), mod[:, 5].clone())
    h = _layernorm(x, axis=-1) * (1 + ca) + sa
    x = x + ga * _A_ref(h, A_k, A_v, A_shift_k, A_ssm_k, A_ssm_D)
    h = _layernorm(x, axis=-1) * (1 + cb) + sb
    x = x + gb * _B_ref(h, B_w1, B_w2)
    return x
```

```cpp
#include <cuda_runtime.h>
#include <cuda_bf16.h>
#include <cuda.h>
#include <stdint.h>

constexpr int S_LEN = 2048;
constexpr int DM    = 512;
constexpr int FF    = 1792;

__device__ __nv_bfloat16 g_yt[S_LEN * DM];
__device__ float         g_mod[6 * DM];
__device__ __nv_bfloat16 g_x1[S_LEN * DM];
__device__ __nv_bfloat16 g_h2[S_LEN * DM];
__device__ __nv_bfloat16 g_H[S_LEN * FF];

__device__ __forceinline__ float rbf(float x) { return __bfloat162float(__float2bfloat16_rn(x)); }
__device__ __forceinline__ float bf_lo(uint32_t u) { return __uint_as_float(u << 16); }
__device__ __forceinline__ float bf_hi(uint32_t u) { return __uint_as_float(u & 0xffff0000u); }
__device__ __forceinline__ uint32_t pack_bf(float lo, float hi) {
  uint32_t r;
  asm("cvt.rn.bf16x2.f32 %0, %1, %2;" : "=r"(r) : "f"(hi), "f"(lo));
  return r;
}
__device__ __forceinline__ uint32_t smem_u32(const void* p) { return (uint32_t)__cvta_generic_to_shared(p); }

__device__ __forceinline__ void wgmma_fence() { asm volatile("wgmma.fence.sync.aligned;\n" ::: "memory"); }
__device__ __forceinline__ void wgmma_commit() { asm volatile("wgmma.commit_group.sync.aligned;\n" ::: "memory"); }
template <int N> __device__ __forceinline__ void wgmma_wait() {
  asm volatile("wgmma.wait_group.sync.aligned %0;\n" ::"n"(N) : "memory");
}
__device__ __forceinline__ void fence_proxy_async() { asm volatile("fence.proxy.async.shared::cta;\n" ::: "memory"); }

__device__ __forceinline__ uint64_t make_desc(uint32_t saddr, uint32_t lbo_bytes, uint32_t sbo_bytes, uint32_t layout) {
  uint64_t d = 0;
  d |= (uint64_t)((saddr & 0x3FFFF) >> 4);
  d |= (uint64_t)((lbo_bytes >> 4) & 0x3FFF) << 16;
  d |= (uint64_t)((sbo_bytes >> 4) & 0x3FFF) << 32;
  d |= (uint64_t)layout << 62;
  return d;
}

template<int N> __device__ __forceinline__ void wgmma_rs(float* d, uint32_t a0, uint32_t a1, uint32_t a2, uint32_t a3, uint64_t descB, int scaleD);
template<> __device__ __forceinline__ void wgmma_rs<8>(float* d, uint32_t a0, uint32_t a1, uint32_t a2, uint32_t a3, uint64_t descB, int scaleD) {
  asm volatile("{\n.reg .pred p;\nsetp.ne.b32 p, %9, 0;\n"
    "wgmma.mma_async.sync.aligned.m64n8k16.f32.bf16.bf16 {%0, %1, %2, %3}, {%4, %5, %6, %7}, %8, p, 1, 1, 0;\n}\n"
    : "+f"(d[0]), "+f"(d[1]), "+f"(d[2]), "+f"(d[3])
    : "r"(a0), "r"(a1), "r"(a2), "r"(a3), "l"(descB), "r"(scaleD));
}
template<> __device__ __forceinline__ void wgmma_rs<16>(float* d, uint32_t a0, uint32_t a1, uint32_t a2, uint32_t a3, uint64_t descB, int scaleD) {
  asm volatile("{\n.reg .pred p;\nsetp.ne.b32 p, %13, 0;\n"
    "wgmma.mma_async.sync.aligned.m64n16k16.f32.bf16.bf16 {%0, %1, %2, %3, %4, %5, %6, %7}, {%8, %9, %10, %11}, %12, p, 1, 1, 0;\n}\n"
    : "+f"(d[0]), "+f"(d[1]), "+f"(d[2]), "+f"(d[3]), "+f"(d[4]), "+f"(d[5]), "+f"(d[6]), "+f"(d[7])
    : "r"(a0), "r"(a1), "r"(a2), "r"(a3), "l"(descB), "r"(scaleD));
}
template<> __device__ __forceinline__ void wgmma_rs<24>(float* d, uint32_t a0, uint32_t a1, uint32_t a2, uint32_t a3, uint64_t descB, int scaleD) {
  asm volatile("{\n.reg .pred p;\nsetp.ne.b32 p, %17, 0;\n"
    "wgmma.mma_async.sync.aligned.m64n24k16.f32.bf16.bf16 {%0, %1, %2, %3, %4, %5, %6, %7, %8, %9, %10, %11}, {%12, %13, %14, %15}, %16, p, 1, 1, 0;\n}\n"
    : "+f"(d[0]), "+f"(d[1]), "+f"(d[2]), "+f"(d[3]), "+f"(d[4]), "+f"(d[5]), "+f"(d[6]), "+f"(d[7]), "+f"(d[8]), "+f"(d[9]), "+f"(d[10]), "+f"(d[11])
    : "r"(a0), "r"(a1), "r"(a2), "r"(a3), "l"(descB), "r"(scaleD));
}
template<> __device__ __forceinline__ void wgmma_rs<32>(float* d, uint32_t a0, uint32_t a1, uint32_t a2, uint32_t a3, uint64_t descB, int scaleD) {
  asm volatile("{\n.reg .pred p;\nsetp.ne.b32 p, %21, 0;\n"
    "wgmma.mma_async.sync.aligned.m64n32k16.f32.bf16.bf16 {%0, %1, %2, %3, %4, %5, %6, %7, %8, %9, %10, %11, %12, %13, %14, %15}, {%16, %17, %18, %19}, %20, p, 1, 1, 0;\n}\n"
    : "+f"(d[0]), "+f"(d[1]), "+f"(d[2]), "+f"(d[3]), "+f"(d[4]), "+f"(d[5]), "+f"(d[6]), "+f"(d[7]), "+f"(d[8]), "+f"(d[9]), "+f"(d[10]), "+f"(d[11]), "+f"(d[12]), "+f"(d[13]), "+f"(d[14]), "+f"(d[15])
    : "r"(a0), "r"(a1), "r"(a2), "r"(a3), "l"(descB), "r"(scaleD));
}
template<> __device__ __forceinline__ void wgmma_rs<40>(float* d, uint32_t a0, uint32_t a1, uint32_t a2, uint32_t a3, uint64_t descB, int scaleD) {
  asm volatile("{\n.reg .pred p;\nsetp.ne.b32 p, %25, 0;\n"
    "wgmma.mma_async.sync.aligned.m64n40k16.f32.bf16.bf16 {%0, %1, %2, %3, %4, %5, %6, %7, %8, %9, %10, %11, %12, %13, %14, %15, %16, %17, %18, %19}, {%20, %21, %22, %23}, %24, p, 1, 1, 0;\n}\n"
    : "+f"(d[0]), "+f"(d[1]), "+f"(d[2]), "+f"(d[3]), "+f"(d[4]), "+f"(d[5]), "+f"(d[6]), "+f"(d[7]), "+f"(d[8]), "+f"(d[9]), "+f"(d[10]), "+f"(d[11]), "+f"(d[12]), "+f"(d[13]), "+f"(d[14]), "+f"(d[15]), "+f"(d[16]), "+f"(d[17]), "+f"(d[18]), "+f"(d[19])
    : "r"(a0), "r"(a1), "r"(a2), "r"(a3), "l"(descB), "r"(scaleD));
}
template<> __device__ __forceinline__ void wgmma_rs<48>(float* d, uint32_t a0, uint32_t a1, uint32_t a2, uint32_t a3, uint64_t descB, int scaleD) {
  asm volatile("{\n.reg .pred p;\nsetp.ne.b32 p, %29, 0;\n"
    "wgmma.mma_async.sync.aligned.m64n48k16.f32.bf16.bf16 {%0, %1, %2, %3, %4, %5, %6, %7, %8, %9, %10, %11, %12, %13, %14, %15, %16, %17, %18, %19, %20, %21, %22, %23}, {%24, %25, %26, %27}, %28, p, 1, 1, 0;\n}\n"
    : "+f"(d[0]), "+f"(d[1]), "+f"(d[2]), "+f"(d[3]), "+f"(d[4]), "+f"(d[5]), "+f"(d[6]), "+f"(d[7]), "+f"(d[8]), "+f"(d[9]), "+f"(d[10]), "+f"(d[11]), "+f"(d[12]), "+f"(d[13]), "+f"(d[14]), "+f"(d[15]), "+f"(d[16]), "+f"(d[17]), "+f"(d[18]), "+f"(d[19]), "+f"(d[20]), "+f"(d[21]), "+f"(d[22]), "+f"(d[23])
    : "r"(a0), "r"(a1), "r"(a2), "r"(a3), "l"(descB), "r"(scaleD));
}
template<> __device__ __forceinline__ void wgmma_rs<56>(float* d, uint32_t a0, uint32_t a1, uint32_t a2, uint32_t a3, uint64_t descB, int scaleD) {
  asm volatile("{\n.reg .pred p;\nsetp.ne.b32 p, %33, 0;\n"
    "wgmma.mma_async.sync.aligned.m64n56k16.f32.bf16.bf16 {%0, %1, %2, %3, %4, %5, %6, %7, %8, %9, %10, %11, %12, %13, %14, %15, %16, %17, %18, %19, %20, %21, %22, %23, %24, %25, %26, %27}, {%28, %29, %30, %31}, %32, p, 1, 1, 0;\n}\n"
    : "+f"(d[0]), "+f"(d[1]), "+f"(d[2]), "+f"(d[3]), "+f"(d[4]), "+f"(d[5]), "+f"(d[6]), "+f"(d[7]), "+f"(d[8]), "+f"(d[9]), "+f"(d[10]), "+f"(d[11]), "+f"(d[12]), "+f"(d[13]), "+f"(d[14]), "+f"(d[15]), "+f"(d[16]), "+f"(d[17]), "+f"(d[18]), "+f"(d[19]), "+f"(d[20]), "+f"(d[21]), "+f"(d[22]), "+f"(d[23]), "+f"(d[24]), "+f"(d[25]), "+f"(d[26]), "+f"(d[27])
    : "r"(a0), "r"(a1), "r"(a2), "r"(a3), "l"(descB), "r"(scaleD));
}
template<> __device__ __forceinline__ void wgmma_rs<64>(float* d, uint32_t a0, uint32_t a1, uint32_t a2, uint32_t a3, uint64_t descB, int scaleD) {
  asm volatile("{\n.reg .pred p;\nsetp.ne.b32 p, %37, 0;\n"
    "wgmma.mma_async.sync.aligned.m64n64k16.f32.bf16.bf16 {%0, %1, %2, %3, %4, %5, %6, %7, %8, %9, %10, %11, %12, %13, %14, %15, %16, %17, %18, %19, %20, %21, %22, %23, %24, %25, %26, %27, %28, %29, %30, %31}, {%32, %33, %34, %35}, %36, p, 1, 1, 0;\n}\n"
    : "+f"(d[0]), "+f"(d[1]), "+f"(d[2]), "+f"(d[3]), "+f"(d[4]), "+f"(d[5]), "+f"(d[6]), "+f"(d[7]), "+f"(d[8]), "+f"(d[9]), "+f"(d[10]), "+f"(d[11]), "+f"(d[12]), "+f"(d[13]), "+f"(d[14]), "+f"(d[15]), "+f"(d[16]), "+f"(d[17]), "+f"(d[18]), "+f"(d[19]), "+f"(d[20]), "+f"(d[21]), "+f"(d[22]), "+f"(d[23]), "+f"(d[24]), "+f"(d[25]), "+f"(d[26]), "+f"(d[27]), "+f"(d[28]), "+f"(d[29]), "+f"(d[30]), "+f"(d[31])
    : "r"(a0), "r"(a1), "r"(a2), "r"(a3), "l"(descB), "r"(scaleD));
}
template<> __device__ __forceinline__ void wgmma_rs<72>(float* d, uint32_t a0, uint32_t a1, uint32_t a2, uint32_t a3, uint64_t descB, int scaleD) {
  asm volatile("{\n.reg .pred p;\nsetp.ne.b32 p, %41, 0;\n"
    "wgmma.mma_async.sync.aligned.m64n72k16.f32.bf16.bf16 {%0, %1, %2, %3, %4, %5, %6, %7, %8, %9, %10, %11, %12, %13, %14, %15, %16, %17, %18, %19, %20, %21, %22, %23, %24, %25, %26, %27, %28, %29, %30, %31, %32, %33, %34, %35}, {%36, %37, %38, %39}, %40, p, 1, 1, 0;\n}\n"
    : "+f"(d[0]), "+f"(d[1]), "+f"(d[2]), "+f"(d[3]), "+f"(d[4]), "+f"(d[5]), "+f"(d[6]), "+f"(d[7]), "+f"(d[8]), "+f"(d[9]), "+f"(d[10]), "+f"(d[11]), "+f"(d[12]), "+f"(d[13]), "+f"(d[14]), "+f"(d[15]), "+f"(d[16]), "+f"(d[17]), "+f"(d[18]), "+f"(d[19]), "+f"(d[20]), "+f"(d[21]), "+f"(d[22]), "+f"(d[23]), "+f"(d[24]), "+f"(d[25]), "+f"(d[26]), "+f"(d[27]), "+f"(d[28]), "+f"(d[29]), "+f"(d[30]), "+f"(d[31]), "+f"(d[32]), "+f"(d[33]), "+f"(d[34]), "+f"(d[35])
    : "r"(a0), "r"(a1), "r"(a2), "r"(a3), "l"(descB), "r"(scaleD));
}
template<> __device__ __forceinline__ void wgmma_rs<80>(float* d, uint32_t a0, uint32_t a1, uint32_t a2, uint32_t a3, uint64_t descB, int scaleD) {
  asm volatile("{\n.reg .pred p;\nsetp.ne.b32 p, %45, 0;\n"
    "wgmma.mma_async.sync.aligned.m64n80k16.f32.bf16.bf16 {%0, %1, %2, %3, %4, %5, %6, %7, %8, %9, %10, %11, %12, %13, %14, %15, %16, %17, %18, %19, %20, %21, %22, %23, %24, %25, %26, %27, %28, %29, %30, %31, %32, %33, %34, %35, %36, %37, %38, %39}, {%40, %41, %42, %43}, %44, p, 1, 1, 0;\n}\n"
    : "+f"(d[0]), "+f"(d[1]), "+f"(d[2]), "+f"(d[3]), "+f"(d[4]), "+f"(d[5]), "+f"(d[6]), "+f"(d[7]), "+f"(d[8]), "+f"(d[9]), "+f"(d[10]), "+f"(d[11]), "+f"(d[12]), "+f"(d[13]), "+f"(d[14]), "+f"(d[15]), "+f"(d[16]), "+f"(d[17]), "+f"(d[18]), "+f"(d[19]), "+f"(d[20]), "+f"(d[21]), "+f"(d[22]), "+f"(d[23]), "+f"(d[24]), "+f"(d[25]), "+f"(d[26]), "+f"(d[27]), "+f"(d[28]), "+f"(d[29]), "+f"(d[30]), "+f"(d[31]), "+f"(d[32]), "+f"(d[33]), "+f"(d[34]), "+f"(d[35]), "+f"(d[36]), "+f"(d[37]), "+f"(d[38]), "+f"(d[39])
    : "r"(a0), "r"(a1), "r"(a2), "r"(a3), "l"(descB), "r"(scaleD));
}
template<> __device__ __forceinline__ void wgmma_rs<88>(float* d, uint32_t a0, uint32_t a1, uint32_t a2, uint32_t a3, uint64_t descB, int scaleD) {
  asm volatile("{\n.reg .pred p;\nsetp.ne.b32 p, %49, 0;\n"
    "wgmma.mma_async.sync.aligned.m64n88k16.f32.bf16.bf16 {%0, %1, %2, %3, %4, %5, %6, %7, %8, %9, %10, %11, %12, %13, %14, %15, %16, %17, %18, %19, %20, %21, %22, %23, %24, %25, %26, %27, %28, %29, %30, %31, %32, %33, %34, %35, %36, %37, %38, %39, %40, %41, %42, %43}, {%44, %45, %46, %47}, %48, p, 1, 1, 0;\n}\n"
    : "+f"(d[0]), "+f"(d[1]), "+f"(d[2]), "+f"(d[3]), "+f"(d[4]), "+f"(d[5]), "+f"(d[6]), "+f"(d[7]), "+f"(d[8]), "+f"(d[9]), "+f"(d[10]), "+f"(d[11]), "+f"(d[12]), "+f"(d[13]), "+f"(d[14]), "+f"(d[15]), "+f"(d[16]), "+f"(d[17]), "+f"(d[18]), "+f"(d[19]), "+f"(d[20]), "+f"(d[21]), "+f"(d[22]), "+f"(d[23]), "+f"(d[24]), "+f"(d[25]), "+f"(d[26]), "+f"(d[27]), "+f"(d[28]), "+f"(d[29]), "+f"(d[30]), "+f"(d[31]), "+f"(d[32]), "+f"(d[33]), "+f"(d[34]), "+f"(d[35]), "+f"(d[36]), "+f"(d[37]), "+f"(d[38]), "+f"(d[39]), "+f"(d[40]), "+f"(d[41]), "+f"(d[42]), "+f"(d[43])
    : "r"(a0), "r"(a1), "r"(a2), "r"(a3), "l"(descB), "r"(scaleD));
}
template<> __device__ __forceinline__ void wgmma_rs<96>(float* d, uint32_t a0, uint32_t a1, uint32_t a2, uint32_t a3, uint64_t descB, int scaleD) {
  asm volatile("{\n.reg .pred p;\nsetp.ne.b32 p, %53, 0;\n"
    "wgmma.mma_async.sync.aligned.m64n96k16.f32.bf16.bf16 {%0, %1, %2, %3, %4, %5, %6, %7, %8, %9, %10, %11, %12, %13, %14, %15, %16, %17, %18, %19, %20, %21, %22, %23, %24, %25, %26, %27, %28, %29, %30, %31, %32, %33, %34, %35, %36, %37, %38, %39, %40, %41, %42, %43, %44, %45, %46, %47}, {%48, %49, %50, %51}, %52, p, 1, 1, 0;\n}\n"
    : "+f"(d[0]), "+f"(d[1]), "+f"(d[2]), "+f"(d[3]), "+f"(d[4]), "+f"(d[5]), "+f"(d[6]), "+f"(d[7]), "+f"(d[8]), "+f"(d[9]), "+f"(d[10]), "+f"(d[11]), "+f"(d[12]), "+f"(d[13]), "+f"(d[14]), "+f"(d[15]), "+f"(d[16]), "+f"(d[17]), "+f"(d[18]), "+f"(d[19]), "+f"(d[20]), "+f"(d[21]), "+f"(d[22]), "+f"(d[23]), "+f"(d[24]), "+f"(d[25]), "+f"(d[26]), "+f"(d[27]), "+f"(d[28]), "+f"(d[29]), "+f"(d[30]), "+f"(d[31]), "+f"(d[32]), "+f"(d[33]), "+f"(d[34]), "+f"(d[35]), "+f"(d[36]), "+f"(d[37]), "+f"(d[38]), "+f"(d[39]), "+f"(d[40]), "+f"(d[41]), "+f"(d[42]), "+f"(d[43]), "+f"(d[44]), "+f"(d[45]), "+f"(d[46]), "+f"(d[47])
    : "r"(a0), "r"(a1), "r"(a2), "r"(a3), "l"(descB), "r"(scaleD));
}
template<> __device__ __forceinline__ void wgmma_rs<104>(float* d, uint32_t a0, uint32_t a1, uint32_t a2, uint32_t a3, uint64_t descB, int scaleD) {
  asm volatile("{\n.reg .pred p;\nsetp.ne.b32 p, %57, 0;\n"
    "wgmma.mma_async.sync.aligned.m64n104k16.f32.bf16.bf16 {%0, %1, %2, %3, %4, %5, %6, %7, %8, %9, %10, %11, %12, %13, %14, %15, %16, %17, %18, %19, %20, %21, %22, %23, %24, %25, %26, %27, %28, %29, %30, %31, %32, %33, %34, %35, %36, %37, %38, %39, %40, %41, %42, %43, %44, %45, %46, %47, %48, %49, %50, %51}, {%52, %53, %54, %55}, %56, p, 1, 1, 0;\n}\n"
    : "+f"(d[0]), "+f"(d[1]), "+f"(d[2]), "+f"(d[3]), "+f"(d[4]), "+f"(d[5]), "+f"(d[6]), "+f"(d[7]), "+f"(d[8]), "+f"(d[9]), "+f"(d[10]), "+f"(d[11]), "+f"(d[12]), "+f"(d[13]), "+f"(d[14]), "+f"(d[15]), "+f"(d[16]), "+f"(d[17]), "+f"(d[18]), "+f"(d[19]), "+f"(d[20]), "+f"(d[21]), "+f"(d[22]), "+f"(d[23]), "+f"(d[24]), "+f"(d[25]), "+f"(d[26]), "+f"(d[27]), "+f"(d[28]), "+f"(d[29]), "+f"(d[30]), "+f"(d[31]), "+f"(d[32]), "+f"(d[33]), "+f"(d[34]), "+f"(d[35]), "+f"(d[36]), "+f"(d[37]), "+f"(d[38]), "+f"(d[39]), "+f"(d[40]), "+f"(d[41]), "+f"(d[42]), "+f"(d[43]), "+f"(d[44]), "+f"(d[45]), "+f"(d[46]), "+f"(d[47]), "+f"(d[48]), "+f"(d[49]), "+f"(d[50]), "+f"(d[51])
    : "r"(a0), "r"(a1), "r"(a2), "r"(a3), "l"(descB), "r"(scaleD));
}
template<> __device__ __forceinline__ void wgmma_rs<112>(float* d, uint32_t a0, uint32_t a1, uint32_t a2, uint32_t a3, uint64_t descB, int scaleD) {
  asm volatile("{\n.reg .pred p;\nsetp.ne.b32 p, %61, 0;\n"
    "wgmma.mma_async.sync.aligned.m64n112k16.f32.bf16.bf16 {%0, %1, %2, %3, %4, %5, %6, %7, %8, %9, %10, %11, %12, %13, %14, %15, %16, %17, %18, %19, %20, %21, %22, %23, %24, %25, %26, %27, %28, %29, %30, %31, %32, %33, %34, %35, %36, %37, %38, %39, %40, %41, %42, %43, %44, %45, %46, %47, %48, %49, %50, %51, %52, %53, %54, %55}, {%56, %57, %58, %59}, %60, p, 1, 1, 0;\n}\n"
    : "+f"(d[0]), "+f"(d[1]), "+f"(d[2]), "+f"(d[3]), "+f"(d[4]), "+f"(d[5]), "+f"(d[6]), "+f"(d[7]), "+f"(d[8]), "+f"(d[9]), "+f"(d[10]), "+f"(d[11]), "+f"(d[12]), "+f"(d[13]), "+f"(d[14]), "+f"(d[15]), "+f"(d[16]), "+f"(d[17]), "+f"(d[18]), "+f"(d[19]), "+f"(d[20]), "+f"(d[21]), "+f"(d[22]), "+f"(d[23]), "+f"(d[24]), "+f"(d[25]), "+f"(d[26]), "+f"(d[27]), "+f"(d[28]), "+f"(d[29]), "+f"(d[30]), "+f"(d[31]), "+f"(d[32]), "+f"(d[33]), "+f"(d[34]), "+f"(d[35]), "+f"(d[36]), "+f"(d[37]), "+f"(d[38]), "+f"(d[39]), "+f"(d[40]), "+f"(d[41]), "+f"(d[42]), "+f"(d[43]), "+f"(d[44]), "+f"(d[45]), "+f"(d[46]), "+f"(d[47]), "+f"(d[48]), "+f"(d[49]), "+f"(d[50]), "+f"(d[51]), "+f"(d[52]), "+f"(d[53]), "+f"(d[54]), "+f"(d[55])
    : "r"(a0), "r"(a1), "r"(a2), "r"(a3), "l"(descB), "r"(scaleD));
}
template<> __device__ __forceinline__ void wgmma_rs<120>(float* d, uint32_t a0, uint32_t a1, uint32_t a2, uint32_t a3, uint64_t descB, int scaleD) {
  asm volatile("{\n.reg .pred p;\nsetp.ne.b32 p, %65, 0;\n"
    "wgmma.mma_async.sync.aligned.m64n120k16.f32.bf16.bf16 {%0, %1, %2, %3, %4, %5, %6, %7, %8, %9, %10, %11, %12, %13, %14, %15, %16, %17, %18, %19, %20, %21, %22, %23, %24, %25, %26, %27, %28, %29, %30, %31, %32, %33, %34, %35, %36, %37, %38, %39, %40, %41, %42, %43, %44, %45, %46, %47, %48, %49, %50, %51, %52, %53, %54, %55, %56, %57, %58, %59}, {%60, %61, %62, %63}, %64, p, 1, 1, 0;\n}\n"
    : "+f"(d[0]), "+f"(d[1]), "+f"(d[2]), "+f"(d[3]), "+f"(d[4]), "+f"(d[5]), "+f"(d[6]), "+f"(d[7]), "+f"(d[8]), "+f"(d[9]), "+f"(d[10]), "+f"(d[11]), "+f"(d[12]), "+f"(d[13]), "+f"(d[14]), "+f"(d[15]), "+f"(d[16]), "+f"(d[17]), "+f"(d[18]), "+f"(d[19]), "+f"(d[20]), "+f"(d[21]), "+f"(d[22]), "+f"(d[23]), "+f"(d[24]), "+f"(d[25]), "+f"(d[26]), "+f"(d[27]), "+f"(d[28]), "+f"(d[29]), "+f"(d[30]), "+f"(d[31]), "+f"(d[32]), "+f"(d[33]), "+f"(d[34]), "+f"(d[35]), "+f"(d[36]), "+f"(d[37]), "+f"(d[38]), "+f"(d[39]), "+f"(d[40]), "+f"(d[41]), "+f"(d[42]), "+f"(d[43]), "+f"(d[44]), "+f"(d[45]), "+f"(d[46]), "+f"(d[47]), "+f"(d[48]), "+f"(d[49]), "+f"(d[50]), "+f"(d[51]), "+f"(d[52]), "+f"(d[53]), "+f"(d[54]), "+f"(d[55]), "+f"(d[56]), "+f"(d[57]), "+f"(d[58]), "+f"(d[59])
    : "r"(a0), "r"(a1), "r"(a2), "r"(a3), "l"(descB), "r"(scaleD));
}
template<> __device__ __forceinline__ void wgmma_rs<128>(float* d, uint32_t a0, uint32_t a1, uint32_t a2, uint32_t a3, uint64_t descB, int scaleD) {
  asm volatile("{\n.reg .pred p;\nsetp.ne.b32 p, %69, 0;\n"
    "wgmma.mma_async.sync.aligned.m64n128k16.f32.bf16.bf16 {%0, %1, %2, %3, %4, %5, %6, %7, %8, %9, %10, %11, %12, %13, %14, %15, %16, %17, %18, %19, %20, %21, %22, %23, %24, %25, %26, %27, %28, %29, %30, %31, %32, %33, %34, %35, %36, %37, %38, %39, %40, %41, %42, %43, %44, %45, %46, %47, %48, %49, %50, %51, %52, %53, %54, %55, %56, %57, %58, %59, %60, %61, %62, %63}, {%64, %65, %66, %67}, %68, p, 1, 1, 0;\n}\n"
    : "+f"(d[0]), "+f"(d[1]), "+f"(d[2]), "+f"(d[3]), "+f"(d[4]), "+f"(d[5]), "+f"(d[6]), "+f"(d[7]), "+f"(d[8]), "+f"(d[9]), "+f"(d[10]), "+f"(d[11]), "+f"(d[12]), "+f"(d[13]), "+f"(d[14]), "+f"(d[15]), "+f"(d[16]), "+f"(d[17]), "+f"(d[18]), "+f"(d[19]), "+f"(d[20]), "+f"(d[21]), "+f"(d[22]), "+f"(d[23]), "+f"(d[24]), "+f"(d[25]), "+f"(d[26]), "+f"(d[27]), "+f"(d[28]), "+f"(d[29]), "+f"(d[30]), "+f"(d[31]), "+f"(d[32]), "+f"(d[33]), "+f"(d[34]), "+f"(d[35]), "+f"(d[36]), "+f"(d[37]), "+f"(d[38]), "+f"(d[39]), "+f"(d[40]), "+f"(d[41]), "+f"(d[42]), "+f"(d[43]), "+f"(d[44]), "+f"(d[45]), "+f"(d[46]), "+f"(d[47]), "+f"(d[48]), "+f"(d[49]), "+f"(d[50]), "+f"(d[51]), "+f"(d[52]), "+f"(d[53]), "+f"(d[54]), "+f"(d[55]), "+f"(d[56]), "+f"(d[57]), "+f"(d[58]), "+f"(d[59]), "+f"(d[60]), "+f"(d[61]), "+f"(d[62]), "+f"(d[63])
    : "r"(a0), "r"(a1), "r"(a2), "r"(a3), "l"(descB), "r"(scaleD));
}
template<int N> __device__ __forceinline__ void wgmma_ss(float* d, uint64_t descA, uint64_t descB, int scaleD);
template<> __device__ __forceinline__ void wgmma_ss<64>(float* d, uint64_t descA, uint64_t descB, int scaleD) {
  asm volatile("{\n.reg .pred p;\nsetp.ne.b32 p, %34, 0;\n"
    "wgmma.mma_async.sync.aligned.m64n64k16.f32.bf16.bf16 {%0, %1, %2, %3, %4, %5, %6, %7, %8, %9, %10, %11, %12, %13, %14, %15, %16, %17, %18, %19, %20, %21, %22, %23, %24, %25, %26, %27, %28, %29, %30, %31}, %32, %33, p, 1, 1, 0, 1;\n}\n"
    : "+f"(d[0]), "+f"(d[1]), "+f"(d[2]), "+f"(d[3]), "+f"(d[4]), "+f"(d[5]), "+f"(d[6]), "+f"(d[7]), "+f"(d[8]), "+f"(d[9]), "+f"(d[10]), "+f"(d[11]), "+f"(d[12]), "+f"(d[13]), "+f"(d[14]), "+f"(d[15]), "+f"(d[16]), "+f"(d[17]), "+f"(d[18]), "+f"(d[19]), "+f"(d[20]), "+f"(d[21]), "+f"(d[22]), "+f"(d[23]), "+f"(d[24]), "+f"(d[25]), "+f"(d[26]), "+f"(d[27]), "+f"(d[28]), "+f"(d[29]), "+f"(d[30]), "+f"(d[31])
    : "l"(descA), "l"(descB), "r"(scaleD));
}
template<> __device__ __forceinline__ void wgmma_ss<128>(float* d, uint64_t descA, uint64_t descB, int scaleD) {
  asm volatile("{\n.reg .pred p;\nsetp.ne.b32 p, %66, 0;\n"
    "wgmma.mma_async.sync.aligned.m64n128k16.f32.bf16.bf16 {%0, %1, %2, %3, %4, %5, %6, %7, %8, %9, %10, %11, %12, %13, %14, %15, %16, %17, %18, %19, %20, %21, %22, %23, %24, %25, %26, %27, %28, %29, %30, %31, %32, %33, %34, %35, %36, %37, %38, %39, %40, %41, %42, %43, %44, %45, %46, %47, %48, %49, %50, %51, %52, %53, %54, %55, %56, %57, %58, %59, %60, %61, %62, %63}, %64, %65, p, 1, 1, 0, 1;\n}\n"
    : "+f"(d[0]), "+f"(d[1]), "+f"(d[2]), "+f"(d[3]), "+f"(d[4]), "+f"(d[5]), "+f"(d[6]), "+f"(d[7]), "+f"(d[8]), "+f"(d[9]), "+f"(d[10]), "+f"(d[11]), "+f"(d[12]), "+f"(d[13]), "+f"(d[14]), "+f"(d[15]), "+f"(d[16]), "+f"(d[17]), "+f"(d[18]), "+f"(d[19]), "+f"(d[20]), "+f"(d[21]), "+f"(d[22]), "+f"(d[23]), "+f"(d[24]), "+f"(d[25]), "+f"(d[26]), "+f"(d[27]), "+f"(d[28]), "+f"(d[29]), "+f"(d[30]), "+f"(d[31]), "+f"(d[32]), "+f"(d[33]), "+f"(d[34]), "+f"(d[35]), "+f"(d[36]), "+f"(d[37]), "+f"(d[38]), "+f"(d[39]), "+f"(d[40]), "+f"(d[41]), "+f"(d[42]), "+f"(d[43]), "+f"(d[44]), "+f"(d[45]), "+f"(d[46]), "+f"(d[47]), "+f"(d[48]), "+f"(d[49]), "+f"(d[50]), "+f"(d[51]), "+f"(d[52]), "+f"(d[53]), "+f"(d[54]), "+f"(d[55]), "+f"(d[56]), "+f"(d[57]), "+f"(d[58]), "+f"(d[59]), "+f"(d[60]), "+f"(d[61]), "+f"(d[62]), "+f"(d[63])
    : "l"(descA), "l"(descB), "r"(scaleD));
}
template<> __device__ __forceinline__ void wgmma_ss<224>(float* d, uint64_t descA, uint64_t descB, int scaleD) {
  asm volatile("{\n.reg .pred p;\nsetp.ne.b32 p, %114, 0;\n"
    "wgmma.mma_async.sync.aligned.m64n224k16.f32.bf16.bf16 {%0, %1, %2, %3, %4, %5, %6, %7, %8, %9, %10, %11, %12, %13, %14, %15, %16, %17, %18, %19, %20, %21, %22, %23, %24, %25, %26, %27, %28, %29, %30, %31, %32, %33, %34, %35, %36, %37, %38, %39, %40, %41, %42, %43, %44, %45, %46, %47, %48, %49, %50, %51, %52, %53, %54, %55, %56, %57, %58, %59, %60, %61, %62, %63, %64, %65, %66, %67, %68, %69, %70, %71, %72, %73, %74, %75, %76, %77, %78, %79, %80, %81, %82, %83, %84, %85, %86, %87, %88, %89, %90, %91, %92, %93, %94, %95, %96, %97, %98, %99, %100, %101, %102, %103, %104, %105, %106, %107, %108, %109, %110, %111}, %112, %113, p, 1, 1, 0, 1;\n}\n"
    : "+f"(d[0]), "+f"(d[1]), "+f"(d[2]), "+f"(d[3]), "+f"(d[4]), "+f"(d[5]), "+f"(d[6]), "+f"(d[7]), "+f"(d[8]), "+f"(d[9]), "+f"(d[10]), "+f"(d[11]), "+f"(d[12]), "+f"(d[13]), "+f"(d[14]), "+f"(d[15]), "+f"(d[16]), "+f"(d[17]), "+f"(d[18]), "+f"(d[19]), "+f"(d[20]), "+f"(d[21]), "+f"(d[22]), "+f"(d[23]), "+f"(d[24]), "+f"(d[25]), "+f"(d[26]), "+f"(d[27]), "+f"(d[28]), "+f"(d[29]), "+f"(d[30]), "+f"(d[31]), "+f"(d[32]), "+f"(d[33]), "+f"(d[34]), "+f"(d[35]), "+f"(d[36]), "+f"(d[37]), "+f"(d[38]), "+f"(d[39]), "+f"(d[40]), "+f"(d[41]), "+f"(d[42]), "+f"(d[43]), "+f"(d[44]), "+f"(d[45]), "+f"(d[46]), "+f"(d[47]), "+f"(d[48]), "+f"(d[49]), "+f"(d[50]), "+f"(d[51]), "+f"(d[52]), "+f"(d[53]), "+f"(d[54]), "+f"(d[55]), "+f"(d[56]), "+f"(d[57]), "+f"(d[58]), "+f"(d[59]), "+f"(d[60]), "+f"(d[61]), "+f"(d[62]), "+f"(d[63]), "+f"(d[64]), "+f"(d[65]), "+f"(d[66]), "+f"(d[67]), "+f"(d[68]), "+f"(d[69]), "+f"(d[70]), "+f"(d[71]), "+f"(d[72]), "+f"(d[73]), "+f"(d[74]), "+f"(d[75]), "+f"(d[76]), "+f"(d[77]), "+f"(d[78]), "+f"(d[79]), "+f"(d[80]), "+f"(d[81]), "+f"(d[82]), "+f"(d[83]), "+f"(d[84]), "+f"(d[85]), "+f"(d[86]), "+f"(d[87]), "+f"(d[88]), "+f"(d[89]), "+f"(d[90]), "+f"(d[91]), "+f"(d[92]), "+f"(d[93]), "+f"(d[94]), "+f"(d[95]), "+f"(d[96]), "+f"(d[97]), "+f"(d[98]), "+f"(d[99]), "+f"(d[100]), "+f"(d[101]), "+f"(d[102]), "+f"(d[103]), "+f"(d[104]), "+f"(d[105]), "+f"(d[106]), "+f"(d[107]), "+f"(d[108]), "+f"(d[109]), "+f"(d[110]), "+f"(d[111])
    : "l"(descA), "l"(descB), "r"(scaleD));
}
template<> __device__ __forceinline__ void wgmma_ss<256>(float* d, uint64_t descA, uint64_t descB, int scaleD) {
  asm volatile("{\n.reg .pred p;\nsetp.ne.b32 p, %130, 0;\n"
    "wgmma.mma_async.sync.aligned.m64n256k16.f32.bf16.bf16 {%0, %1, %2, %3, %4, %5, %6, %7, %8, %9, %10, %11, %12, %13, %14, %15, %16, %17, %18, %19, %20, %21, %22, %23, %24, %25, %26, %27, %28, %29, %30, %31, %32, %33, %34, %35, %36, %37, %38, %39, %40, %41, %42, %43, %44, %45, %46, %47, %48, %49, %50, %51, %52, %53, %54, %55, %56, %57, %58, %59, %60, %61, %62, %63, %64, %65, %66, %67, %68, %69, %70, %71, %72, %73, %74, %75, %76, %77, %78, %79, %80, %81, %82, %83, %84, %85, %86, %87, %88, %89, %90, %91, %92, %93, %94, %95, %96, %97, %98, %99, %100, %101, %102, %103, %104, %105, %106, %107, %108, %109, %110, %111, %112, %113, %114, %115, %116, %117, %118, %119, %120, %121, %122, %123, %124, %125, %126, %127}, %128, %129, p, 1, 1, 0, 1;\n}\n"
    : "+f"(d[0]), "+f"(d[1]), "+f"(d[2]), "+f"(d[3]), "+f"(d[4]), "+f"(d[5]), "+f"(d[6]), "+f"(d[7]), "+f"(d[8]), "+f"(d[9]), "+f"(d[10]), "+f"(d[11]), "+f"(d[12]), "+f"(d[13]), "+f"(d[14]), "+f"(d[15]), "+f"(d[16]), "+f"(d[17]), "+f"(d[18]), "+f"(d[19]), "+f"(d[20]), "+f"(d[21]), "+f"(d[22]), "+f"(d[23]), "+f"(d[24]), "+f"(d[25]), "+f"(d[26]), "+f"(d[27]), "+f"(d[28]), "+f"(d[29]), "+f"(d[30]), "+f"(d[31]), "+f"(d[32]), "+f"(d[33]), "+f"(d[34]), "+f"(d[35]), "+f"(d[36]), "+f"(d[37]), "+f"(d[38]), "+f"(d[39]), "+f"(d[40]), "+f"(d[41]), "+f"(d[42]), "+f"(d[43]), "+f"(d[44]), "+f"(d[45]), "+f"(d[46]), "+f"(d[47]), "+f"(d[48]), "+f"(d[49]), "+f"(d[50]), "+f"(d[51]), "+f"(d[52]), "+f"(d[53]), "+f"(d[54]), "+f"(d[55]), "+f"(d[56]), "+f"(d[57]), "+f"(d[58]), "+f"(d[59]), "+f"(d[60]), "+f"(d[61]), "+f"(d[62]), "+f"(d[63]), "+f"(d[64]), "+f"(d[65]), "+f"(d[66]), "+f"(d[67]), "+f"(d[68]), "+f"(d[69]), "+f"(d[70]), "+f"(d[71]), "+f"(d[72]), "+f"(d[73]), "+f"(d[74]), "+f"(d[75]), "+f"(d[76]), "+f"(d[77]), "+f"(d[78]), "+f"(d[79]), "+f"(d[80]), "+f"(d[81]), "+f"(d[82]), "+f"(d[83]), "+f"(d[84]), "+f"(d[85]), "+f"(d[86]), "+f"(d[87]), "+f"(d[88]), "+f"(d[89]), "+f"(d[90]), "+f"(d[91]), "+f"(d[92]), "+f"(d[93]), "+f"(d[94]), "+f"(d[95]), "+f"(d[96]), "+f"(d[97]), "+f"(d[98]), "+f"(d[99]), "+f"(d[100]), "+f"(d[101]), "+f"(d[102]), "+f"(d[103]), "+f"(d[104]), "+f"(d[105]), "+f"(d[106]), "+f"(d[107]), "+f"(d[108]), "+f"(d[109]), "+f"(d[110]), "+f"(d[111]), "+f"(d[112]), "+f"(d[113]), "+f"(d[114]), "+f"(d[115]), "+f"(d[116]), "+f"(d[117]), "+f"(d[118]), "+f"(d[119]), "+f"(d[120]), "+f"(d[121]), "+f"(d[122]), "+f"(d[123]), "+f"(d[124]), "+f"(d[125]), "+f"(d[126]), "+f"(d[127])
    : "l"(descA), "l"(descB), "r"(scaleD));
}


constexpr int K1_THREADS = 512;
constexpr int U_ROWS  = 136;
constexpr int U_PLANE = U_ROWS * 16;
constexpr int U_CH    = 2 * U_PLANE;
constexpr int F_LEN   = 2048 + 32;
constexpr int F_COPY  = F_LEN * 2;
constexpr int F_CH    = 2 * F_COPY;
constexpr int P_CH    = 4 * 2048 * 4;
constexpr int K1_OFF_U = 0;
constexpr int K1_OFF_F = K1_OFF_U + 4 * U_CH;
constexpr int K1_OFF_P = K1_OFF_F + 4 * F_CH;
constexpr int K1_OFF_R = K1_OFF_P + 4 * P_CH;
constexpr int K1_SMEM  = K1_OFF_R + 8 * 32 * 4;

template <int T> struct ConvStep {
  static __device__ __forceinline__ void run(float* acc, const uint32_t* fp, uint32_t ubase) {
    constexpr int N = 128 - 8 * T;
    uint32_t a0 = fp[64 * T], a1 = fp[64 * T + 4], a3 = fp[64 * T + 8];
    uint32_t b0 = fp[64 * T + 32], b1 = fp[64 * T + 36], b3 = fp[64 * T + 40];
    uint64_t d0 = make_desc(ubase + 8 * 16, U_PLANE, 128, 0);
    uint64_t d1 = make_desc(ubase + 4 * 16, U_PLANE, 128, 0);
    wgmma_fence();
    wgmma_rs<N>(acc + 4 * T, a0, a1, a1, a3, d0, T == 0 ? 0 : 1);
    wgmma_rs<N>(acc + 4 * T, b0, b1, b1, b3, d1, 1);
    wgmma_commit();
    wgmma_wait<0>();
    asm volatile("" ::"r"(a0), "r"(a1), "r"(a3), "r"(b0), "r"(b1), "r"(b3));
    ConvStep<T + 1>::run(acc, fp, ubase);
  }
};
template <> struct ConvStep<16> {
  static __device__ __forceinline__ void run(float*, const uint32_t*, uint32_t) {}
};

__global__ void __launch_bounds__(K1_THREADS, 1)
conv_mod_kernel(const __nv_bfloat16* __restrict__ kin, const __nv_bfloat16* __restrict__ vin,
                const __nv_bfloat16* __restrict__ shift_k, const __nv_bfloat16* __restrict__ ssm_k,
                const __nv_bfloat16* __restrict__ ssm_D, const __nv_bfloat16* __restrict__ cvec,
                const __nv_bfloat16* __restrict__ w_mod) {
  extern __shared__ __align__(1024) uint8_t smem[];
  const int tid = threadIdx.x;
  const int d0 = blockIdx.x * 4;

  if (tid < 256) {
    const int a = tid >> 1, h = tid & 1;
    const int s0 = 16 * a + 8 * h;
    uint2 kr[11], vr[8];
#pragma unroll
    for (int i = 0; i < 11; i++) {
      int s = s0 - 3 + i;
      kr[i] = (s >= 0) ? __ldg(reinterpret_cast<const uint2*>(kin + (size_t)s * DM + d0)) : make_uint2(0, 0);
    }
#pragma unroll
    for (int i = 0; i < 8; i++) vr[i] = __ldg(reinterpret_cast<const uint2*>(vin + (size_t)(s0 + i) * DM + d0));
    uint4 w01 = __ldg(reinterpret_cast<const uint4*>(shift_k + d0 * 4));
    uint4 w23 = __ldg(reinterpret_cast<const uint4*>(shift_k + d0 * 4 + 8));
    uint32_t wraw[8] = {w01.x, w01.y, w01.z, w01.w, w23.x, w23.y, w23.z, w23.w};
#pragma unroll
    for (int c = 0; c < 4; c++) {
      const float w0 = bf_lo(wraw[2 * c]), w1 = bf_hi(wraw[2 * c]);
      const float w2 = bf_lo(wraw[2 * c + 1]), w3 = bf_hi(wraw[2 * c + 1]);
      float kf[11];
#pragma unroll
      for (int i = 0; i < 11; i++) {
        uint32_t u = (c < 2) ? kr[i].x : kr[i].y;
        kf[i] = (c & 1) ? bf_hi(u) : bf_lo(u);
      }
      float kv[8];
#pragma unroll
      for (int i = 0; i < 8; i++) {
        float ks = rbf(kf[i] * w3);
        ks = rbf(ks + rbf(kf[i + 1] * w2));
        ks = rbf(ks + rbf(kf[i + 2] * w1));
        ks = rbf(ks + rbf(kf[i + 3] * w0));
        uint32_t u = (c < 2) ? vr[i].x : vr[i].y;
        float vf = (c & 1) ? bf_hi(u) : bf_lo(u);
        kv[i] = ks * vf;
      }
      uint4 o;
      o.x = pack_bf(kv[7], kv[6]);
      o.y = pack_bf(kv[5], kv[4]);
      o.z = pack_bf(kv[3], kv[2]);
      o.w = pack_bf(kv[1], kv[0]);
      *reinterpret_cast<uint4*>(smem + K1_OFF_U + c * U_CH + (1 - h) * U_PLANE + (a + 8) * 16) = o;
    }
    if (tid < 64) {
      int c = tid >> 4, pl = (tid >> 3) & 1, r = tid & 7;
      *reinterpret_cast<uint4*>(smem + K1_OFF_U + c * U_CH + pl * U_PLANE + r * 16) = make_uint4(0, 0, 0, 0);
    }
  } else {
    const int j = tid - 256;
    uint4 fv[4];
    uint32_t fx[4];
#pragma unroll
    for (int c = 0; c < 4; c++) {
      const __nv_bfloat16* fr = ssm_k + (size_t)(d0 + c) * S_LEN;
      fv[c] = __ldg(reinterpret_cast<const uint4*>(fr + 8 * j));
      fx[c] = (j < 255) ? (uint32_t)__ldg(reinterpret_cast<const unsigned short*>(fr + 8 * j + 8)) : 0u;
    }
    float macc[8];
    const bool do_gemv = blockIdx.x < 96;
    if (do_gemv) {
      const int vec = j & 3, rg = j >> 2;
      uint4 wv[8];
      float sc[8];
#pragma unroll
      for (int i = 0; i < 8; i++) {
        int row = rg + 64 * i;
        wv[i] = __ldg(reinterpret_cast<const uint4*>(w_mod + (size_t)row * (6 * DM) + blockIdx.x * 32 + vec * 8));
        float cf = __bfloat162float(cvec[row]);
        sc[i] = rbf(cf / (1.0f + __expf(-cf)));
      }
#pragma unroll
      for (int e = 0; e < 8; e++) macc[e] = 0.f;
#pragma unroll
      for (int i = 0; i < 8; i++) {
        macc[0] += sc[i] * bf_lo(wv[i].x); macc[1] += sc[i] * bf_hi(wv[i].x);
        macc[2] += sc[i] * bf_lo(wv[i].y); macc[3] += sc[i] * bf_hi(wv[i].y);
        macc[4] += sc[i] * bf_lo(wv[i].z); macc[5] += sc[i] * bf_hi(wv[i].z);
        macc[6] += sc[i] * bf_lo(wv[i].w); macc[7] += sc[i] * bf_hi(wv[i].w);
      }
#pragma unroll
      for (int e = 0; e < 8; e++) {
        macc[e] += __shfl_xor_sync(0xffffffffu, macc[e], 4);
        macc[e] += __shfl_xor_sync(0xffffffffu, macc[e], 8);
        macc[e] += __shfl_xor_sync(0xffffffffu, macc[e], 16);
      }
      float* red = reinterpret_cast<float*>(smem + K1_OFF_R);
      if ((j & 31) < 4) {
#pragma unroll
        for (int e = 0; e < 8; e++) red[(j >> 5) * 32 + vec * 8 + e] = macc[e];
      }
    }
#pragma unroll
    for (int c = 0; c < 4; c++) {
      uint8_t* f0 = smem + K1_OFF_F + c * F_CH;
      uint8_t* f1 = f0 + F_COPY;
      *reinterpret_cast<uint4*>(f0 + 32 + 16 * j) = fv[c];
      uint4 sh;
      sh.x = __funnelshift_r(fv[c].x, fv[c].y, 16);
      sh.y = __funnelshift_r(fv[c].y, fv[c].z, 16);
      sh.z = __funnelshift_r(fv[c].z, fv[c].w, 16);
      sh.w = __funnelshift_r(fv[c].w, fx[c], 16);
      *reinterpret_cast<uint4*>(f1 + 32 + 16 * j) = sh;
      if (j == 0) {
        *reinterpret_cast<uint4*>(f0) = make_uint4(0, 0, 0, 0);
        *reinterpret_cast<uint4*>(f0 + 16) = make_uint4(0, 0, 0, 0);
        *reinterpret_cast<uint4*>(f1) = make_uint4(0, 0, 0, 0);
        *reinterpret_cast<uint4*>(f1 + 16) = make_uint4(0, 0, 0, fv[c].x << 16);
      }
      if (j == 1) {
        *reinterpret_cast<uint4*>(f0 + 32 + 4096) = make_uint4(0, 0, 0, 0);
        *reinterpret_cast<uint4*>(f0 + 32 + 4096 + 16) = make_uint4(0, 0, 0, 0);
        *reinterpret_cast<uint4*>(f1 + 32 + 4096) = make_uint4(0, 0, 0, 0);
        *reinterpret_cast<uint4*>(f1 + 32 + 4096 + 16) = make_uint4(0, 0, 0, 0);
      }
    }
  }
  fence_proxy_async();
  __syncthreads();

  if (blockIdx.x < 96 && tid < 32) {
    const float* red = reinterpret_cast<const float*>(smem + K1_OFF_R);
    float s = 0.f;
#pragma unroll
    for (int w = 0; w < 8; w++) s += red[w * 32 + tid];
    g_mod[blockIdx.x * 32 + tid] = rbf(s);
  }

  const int warp = tid >> 5, lane = tid & 31;
  const int c = warp >> 2, w = warp & 3;
  const int g8 = lane >> 2, t4 = lane & 3;
  {
    const int x0 = 16 * w + g8 + 2 * t4 - 15;
    const int par = x0 & 1;
    const uint32_t* fp = reinterpret_cast<const uint32_t*>(smem + K1_OFF_F + c * F_CH + par * F_COPY) + ((16 + x0 - par) >> 1);
    float acc[64];
    const uint32_t ubase = smem_u32(smem + K1_OFF_U + c * U_CH);
    ConvStep<0>::run(acc, fp, ubase);
    float* P = reinterpret_cast<float*>(smem + K1_OFF_P + c * P_CH) + w * 2048;
#pragma unroll
    for (int jj = 0; jj < 16; jj++) {
#pragma unroll
      for (int e = 0; e < 2; e++) {
#pragma unroll
        for (int hi = 0; hi < 2; hi++) {
          int col = (16 * e + g8 + 8 * hi) ^ (8 * t4);
          P[(4 * jj + t4) * 32 + col] = acc[4 * jj + e + 2 * hi];
        }
      }
    }
  }
  __syncthreads();

  float Dc[4];
  {
    uint2 dr = __ldg(reinterpret_cast<const uint2*>(ssm_D + d0));
    Dc[0] = bf_lo(dr.x); Dc[1] = bf_hi(dr.x); Dc[2] = bf_lo(dr.y); Dc[3] = bf_hi(dr.y);
  }
#pragma unroll
  for (int i = 0; i < 4; i++) {
    const int s = tid + 512 * i;
    float yt[4];
#pragma unroll
    for (int cc = 0; cc < 4; cc++) {
      const float* P = reinterpret_cast<const float*>(smem + K1_OFF_P + cc * P_CH);
      float sum = 0.f;
#pragma unroll
      for (int ww = 0; ww < 4; ww++) {
        int sp = s - 16 * ww;
        if (sp >= 0) {
          int aa = sp >> 4, rr = sp & 15;
          int col = (16 * (aa & 1) + rr) ^ (8 * ((aa >> 1) & 3));
          sum += P[ww * 2048 + (aa >> 1) * 32 + col];
        }
      }
      const int kidx = 15 - (s & 15);
      const __nv_bfloat16* up = reinterpret_cast<const __nv_bfloat16*>(
          smem + K1_OFF_U + cc * U_CH + (kidx >> 3) * U_PLANE + ((s >> 4) + 8) * 16);
      float kv = __bfloat162float(up[kidx & 7]);
      yt[cc] = rbf(sum) + rbf(kv * Dc[cc]);
    }
    uint2 o;
    o.x = pack_bf(yt[0], yt[1]);
    o.y = pack_bf(yt[2], yt[3]);
    *reinterpret_cast<uint2*>(g_yt + (size_t)s * DM + d0) = o;
  }
}

__global__ void __launch_bounds__(256) ln_kernel(const __nv_bfloat16* __restrict__ q) {
  const int warp = threadIdx.x >> 5, lane = threadIdx.x & 31;
  const int s = blockIdx.x * 8 + warp;
  float x[16], yt[16];
  {
    uint4 qa = __ldg(reinterpret_cast<const uint4*>(q + (size_t)s * DM + lane * 8));
    uint4 qb = __ldg(reinterpret_cast<const uint4*>(q + (size_t)s * DM + 256 + lane * 8));
    uint4 ya = *reinterpret_cast<const uint4*>(g_yt + (size_t)s * DM + lane * 8);
    uint4 yb = *reinterpret_cast<const uint4*>(g_yt + (size_t)s * DM + 256 + lane * 8);
    uint32_t qq[8] = {qa.x, qa.y, qa.z, qa.w, qb.x, qb.y, qb.z, qb.w};
    uint32_t yy[8] = {ya.x, ya.y, ya.z, ya.w, yb.x, yb.y, yb.z, yb.w};
#pragma unroll
    for (int i = 0; i < 8; i++) {
      x[2 * i] = bf_lo(qq[i]); x[2 * i + 1] = bf_hi(qq[i]);
      yt[2 * i] = bf_lo(yy[i]); yt[2 * i + 1] = bf_hi(yy[i]);
    }
  }
  auto col_of = [&](int i) { return (i < 8) ? (lane * 8 + i) : (256 + lane * 8 + (i - 8)); };
  float sum = 0.f;
#pragma unroll
  for (int i = 0; i < 16; i++) sum += x[i];
#pragma unroll
  for (int o = 16; o > 0; o >>= 1) sum += __shfl_xor_sync(0xffffffffu, sum, o);
  float mean = sum * (1.0f / DM);
  float vs = 0.f;
#pragma unroll
  for (int i = 0; i < 16; i++) { float d = x[i] - mean; vs += d * d; }
#pragma unroll
  for (int o = 16; o > 0; o >>= 1) vs += __shfl_xor_sync(0xffffffffu, vs, o);
  float mb = rbf(mean);
  float den = rbf(sqrtf(rbf(rbf(vs * (1.0f / DM)) + 1e-5f)));
  float x1[16];
#pragma unroll
  for (int i = 0; i < 16; i++) {
    int cidx = col_of(i);
    float sa = g_mod[cidx], ca = g_mod[DM + cidx], ga = g_mod[2 * DM + cidx];
    float ln = rbf(rbf(x[i] - mb) / den);
    float h = rbf(rbf(ln * rbf(1.0f + ca)) + sa);
    float av = rbf(h * yt[i]);
    x1[i] = rbf(x[i] + rbf(ga * av));
  }
  sum = 0.f;
#pragma unroll
  for (int i = 0; i < 16; i++) sum += x1[i];
#pragma unroll
  for (int o = 16; o > 0; o >>= 1) sum += __shfl_xor_sync(0xffffffffu, sum, o);
  mean = sum * (1.0f / DM);
  vs = 0.f;
#pragma unroll
  for (int i = 0; i < 16; i++) { float d = x1[i] - mean; vs += d * d; }
#pragma unroll
  for (int o = 16; o > 0; o >>= 1) vs += __shfl_xor_sync(0xffffffffu, vs, o);
  mb = rbf(mean);
  den = rbf(sqrtf(rbf(rbf(vs * (1.0f / DM)) + 1e-5f)));
  float h2[16];
#pragma unroll
  for (int i = 0; i < 16; i++) {
    int cidx = col_of(i);
    float sb = g_mod[3 * DM + cidx], cb = g_mod[4 * DM + cidx];
    float ln = rbf(rbf(x1[i] - mb) / den);
    h2[i] = rbf(rbf(ln * rbf(1.0f + cb)) + sb);
  }
  uint4 o;
  o.x = pack_bf(x1[0], x1[1]); o.y = pack_bf(x1[2], x1[3]); o.z = pack_bf(x1[4], x1[5]); o.w = pack_bf(x1[6], x1[7]);
  *reinterpret_cast<uint4*>(g_x1 + (size_t)s * DM + lane * 8) = o;
  o.x = pack_bf(x1[8], x1[9]); o.y = pack_bf(x1[10], x1[11]); o.z = pack_bf(x1[12], x1[13]); o.w = pack_bf(x1[14], x1[15]);
  *reinterpret_cast<uint4*>(g_x1 + (size_t)s * DM + 256 + lane * 8) = o;
  o.x = pack_bf(h2[0], h2[1]); o.y = pack_bf(h2[2], h2[3]); o.z = pack_bf(h2[4], h2[5]); o.w = pack_bf(h2[6], h2[7]);
  *reinterpret_cast<uint4*>(g_h2 + (size_t)s * DM + lane * 8) = o;
  o.x = pack_bf(h2[8], h2[9]); o.y = pack_bf(h2[10], h2[11]); o.z = pack_bf(h2[12], h2[13]); o.w = pack_bf(h2[14], h2[15]);
  *reinterpret_cast<uint4*>(g_h2 + (size_t)s * DM + 256 + lane * 8) = o;
}

__device__ __forceinline__ void mbar_init(uint32_t bar, uint32_t count) {
  asm volatile("mbarrier.init.shared::cta.b64 [%0], %1;" ::"r"(bar), "r"(count) : "memory");
}
__device__ __forceinline__ void mbar_expect_tx(uint32_t bar, uint32_t bytes) {
  asm volatile("mbarrier.arrive.expect_tx.shared::cta.b64 _, [%0], %1;" ::"r"(bar), "r"(bytes) : "memory");
}
__device__ __forceinline__ void mbar_arrive(uint32_t bar) {
  asm volatile("mbarrier.arrive.shared::cta.b64 _, [%0];" ::"r"(bar) : "memory");
}
__device__ __forceinline__ void mbar_wait(uint32_t bar, uint32_t parity) {
  asm volatile(
      "{\n.reg .pred p;\n"
      "WAIT_LOOP:\n"
      "mbarrier.try_wait.parity.shared::cta.b64 p, [%0], %1, 0x989680;\n"
      "@p bra WAIT_DONE;\n"
      "bra WAIT_LOOP;\n"
      "WAIT_DONE:\n}\n" ::"r"(bar), "r"(parity) : "memory");
}
__device__ __forceinline__ void tma_load_2d(uint32_t dst, const CUtensorMap* tm, uint32_t bar, int c0, int c1) {
  asm volatile(
      "cp.async.bulk.tensor.2d.shared::cluster.global.mbarrier::complete_tx::bytes [%0], [%1, {%3, %4}], [%2];"
      ::"r"(dst), "l"(reinterpret_cast<uint64_t>(tm)), "r"(bar), "r"(c0), "r"(c1) : "memory");
}

template <int BN, int STAGES, int EPI>
__global__ void __launch_bounds__(384, 1)
gemm_kernel(const __grid_constant__ CUtensorMap tmA, const __grid_constant__ CUtensorMap tmB, int K,
            __nv_bfloat16* __restrict__ outp, int ldo) {
  constexpr int A_BYTES = 128 * 64 * 2;
  constexpr int B_BYTES = BN * 64 * 2;
  constexpr int STAGE_BYTES = A_BYTES + B_BYTES;
  extern __shared__ __align__(1024) uint8_t smem[];
  __shared__ __align__(8) uint64_t bars[2 * STAGES];
  const int tid = threadIdx.x, warp = tid >> 5, lane = tid & 31;
  const int m0 = blockIdx.y * 128, n0 = blockIdx.x * BN;
  const uint32_t sbase = smem_u32(smem);
  const uint32_t full0 = smem_u32(&bars[0]), empty0 = smem_u32(&bars[STAGES]);
  if (tid == 0) {
    for (int i = 0; i < STAGES; i++) { mbar_init(full0 + 8 * i, 1); mbar_init(empty0 + 8 * i, 2); }
    asm volatile("fence.mbarrier_init.release.cluster;" ::: "memory");
  }
  __syncthreads();
  const int nkb = K / 64;
  if (warp >= 8) {
    if (warp == 8 && lane == 0) {
      for (int kb = 0; kb < nkb; kb++) {
        const int st = kb % STAGES;
        mbar_wait(empty0 + 8 * st, ((kb / STAGES) & 1) ^ 1);
        mbar_expect_tx(full0 + 8 * st, STAGE_BYTES);
        const uint32_t sa = sbase + st * STAGE_BYTES;
        tma_load_2d(sa, &tmA, full0 + 8 * st, kb * 64, m0);
#pragma unroll
        for (int nb = 0; nb < BN / 64; nb++)
          tma_load_2d(sa + A_BYTES + nb * 8192, &tmB, full0 + 8 * st, n0 + nb * 64, kb * 64);
      }
    }
  } else {
    const int wg = warp >> 2;
    float acc[BN / 2];
    for (int kb = 0; kb < nkb; kb++) {
      const int st = kb % STAGES;
      mbar_wait(full0 + 8 * st, (kb / STAGES) & 1);
      const uint32_t sa = sbase + st * STAGE_BYTES;
      wgmma_fence();
#pragma unroll
      for (int k = 0; k < 4; k++) {
        uint64_t dA = make_desc(sa + wg * 8192 + k * 32, 16, 1024, 1);
        uint64_t dB = make_desc(sa + A_BYTES + k * 2048, 8192, 1024, 1);
        wgmma_ss<BN>(acc, dA, dB, (kb > 0 || k > 0) ? 1 : 0);
      }
      wgmma_commit();
      if (kb > 0) {
        wgmma_wait<1>();
        if ((tid & 127) == 0) mbar_arrive(empty0 + 8 * ((kb - 1) % STAGES));
      }
    }
    wgmma_wait<0>();
    asm volatile("bar.sync 1, 256;" ::: "memory");
    constexpr int ROWB = BN * 2 + 16;
    uint8_t* stg = smem + wg * (64 * ROWB);
    const int w4 = warp & 3, g8 = lane >> 2, t4 = lane & 3;
#pragma unroll
    for (int j = 0; j < BN / 8; j++) {
      float v0 = acc[4 * j], v1 = acc[4 * j + 1], v2 = acc[4 * j + 2], v3 = acc[4 * j + 3];
      if (EPI == 0) {
        v0 = rbf(v0); v1 = rbf(v1); v2 = rbf(v2); v3 = rbf(v3);
        v0 = v0 / (1.0f + __expf(-v0)); v1 = v1 / (1.0f + __expf(-v1));
        v2 = v2 / (1.0f + __expf(-v2)); v3 = v3 / (1.0f + __expf(-v3));
      } else {
        const int cidx = n0 + 8 * j + 2 * t4;
        const float gb0 = g_mod[5 * DM + cidx], gb1 = g_mod[5 * DM + cidx + 1];
        v0 = gb0 * rbf(v0); v1 = gb1 * rbf(v1); v2 = gb0 * rbf(v2); v3 = gb1 * rbf(v3);
      }
      *reinterpret_cast<uint32_t*>(stg + (16 * w4 + g8) * ROWB + (8 * j + 2 * t4) * 2) = pack_bf(v0, v1);
      *reinterpret_cast<uint32_t*>(stg + (16 * w4 + g8 + 8) * ROWB + (8 * j + 2 * t4) * 2) = pack_bf(v2, v3);
    }
    asm volatile("bar.sync %0, 128;" ::"r"(2 + wg) : "memory");
    constexpr int VEC_PER_ROW = BN / 8;
    const int t = tid & 127;
#pragma unroll 4
    for (int idx = t; idx < 64 * VEC_PER_ROW; idx += 128) {
      const int r = idx / VEC_PER_ROW, cv = idx % VEC_PER_ROW;
      uint4 v = *reinterpret_cast<const uint4*>(stg + r * ROWB + cv * 16);
      const size_t goff = (size_t)(m0 + wg * 64 + r) * ldo + n0 + cv * 8;
      if (EPI == 1) {
        uint4 xr = *reinterpret_cast<const uint4*>(g_x1 + goff);
        uint32_t vv[4] = {v.x, v.y, v.z, v.w}, xx[4] = {xr.x, xr.y, xr.z, xr.w}, oo[4];
#pragma unroll
        for (int e = 0; e < 4; e++) oo[e] = pack_bf(bf_lo(xx[e]) + bf_lo(vv[e]), bf_hi(xx[e]) + bf_hi(vv[e]));
        v = make_uint4(oo[0], oo[1], oo[2], oo[3]);
      }
      *reinterpret_cast<uint4*>(outp + goff) = v;
    }
  }
}

typedef CUresult (*PFN_encodeTiled)(CUtensorMap*, CUtensorMapDataType, cuuint32_t, void*, const cuuint64_t*,
                                    const cuuint64_t*, const cuuint32_t*, const cuuint32_t*, CUtensorMapInterleave,
                                    CUtensorMapSwizzle, CUtensorMapL2promotion, CUtensorMapFloatOOBfill);

static void make_tmap(PFN_encodeTiled enc, CUtensorMap* tm, void* ptr, uint64_t inner, uint64_t outer,
                      uint32_t box_inner, uint32_t box_outer) {
  cuuint64_t gdim[2] = {inner, outer};
  cuuint64_t gstr[1] = {inner * 2};
  cuuint32_t box[2] = {box_inner, box_outer};
  cuuint32_t estr[2] = {1, 1};
  enc(tm, CU_TENSOR_MAP_DATA_TYPE_BFLOAT16, 2, ptr, gdim, gstr, box, estr, CU_TENSOR_MAP_INTERLEAVE_NONE,
      CU_TENSOR_MAP_SWIZZLE_128B, CU_TENSOR_MAP_L2_PROMOTION_L2_256B, CU_TENSOR_MAP_FLOAT_OOB_FILL_NONE);
}

constexpr int G1_BN = 256, G1_STAGES = 4;
constexpr int G2_BN = 64, G2_STAGES = 6;

extern "C" void kernel_launch(void* const* d_in, const int* in_sizes, int n_in, void* d_out, int out_size) {
  const __nv_bfloat16* A_q = (const __nv_bfloat16*)d_in[0];
  const __nv_bfloat16* A_k = (const __nv_bfloat16*)d_in[1];
  const __nv_bfloat16* A_v = (const __nv_bfloat16*)d_in[2];
  const __nv_bfloat16* A_shift = (const __nv_bfloat16*)d_in[3];
  const __nv_bfloat16* A_ssmk = (const __nv_bfloat16*)d_in[4];
  const __nv_bfloat16* A_ssmD = (const __nv_bfloat16*)d_in[5];
  const __nv_bfloat16* B_w1 = (const __nv_bfloat16*)d_in[7];
  const __nv_bfloat16* B_w2 = (const __nv_bfloat16*)d_in[8];
  const __nv_bfloat16* cvec = (const __nv_bfloat16*)d_in[9];
  const __nv_bfloat16* w_mod = (const __nv_bfloat16*)d_in[10];

  CUtensorMap tmA1, tmB1, tmA2, tmB2;
  {
    PFN_encodeTiled enc = nullptr;
    cudaDriverEntryPointQueryResult qr;
    cudaGetDriverEntryPoint("cuTensorMapEncodeTiled", (void**)&enc, cudaEnableDefault, &qr);
    void *ph2, *pH;
    cudaGetSymbolAddress(&ph2, g_h2);
    cudaGetSymbolAddress(&pH, g_H);
    make_tmap(enc, &tmA1, ph2, DM, S_LEN, 64, 128);
    make_tmap(enc, &tmB1, (void*)B_w1, FF, DM, 64, 64);
    make_tmap(enc, &tmA2, pH, FF, S_LEN, 64, 128);
    make_tmap(enc, &tmB2, (void*)B_w2, DM, FF, 64, 64);
    cudaFuncSetAttribute(conv_mod_kernel, cudaFuncAttributeMaxDynamicSharedMemorySize, K1_SMEM);
    cudaFuncSetAttribute(gemm_kernel<G1_BN, G1_STAGES, 0>, cudaFuncAttributeMaxDynamicSharedMemorySize,
                         G1_STAGES * (16384 + G1_BN * 128));
    cudaFuncSetAttribute(gemm_kernel<G2_BN, G2_STAGES, 1>, cudaFuncAttributeMaxDynamicSharedMemorySize,
                         G2_STAGES * (16384 + G2_BN * 128));
  }
  __nv_bfloat16* gH;
  cudaGetSymbolAddress((void**)&gH, g_H);

  conv_mod_kernel<<<128, K1_THREADS, K1_SMEM>>>(A_k, A_v, A_shift, A_ssmk, A_ssmD, cvec, w_mod);
  ln_kernel<<<256, 256>>>(A_q);
  gemm_kernel<G1_BN, G1_STAGES, 0><<<dim3(FF / G1_BN, S_LEN / 128), 384, G1_STAGES * (16384 + G1_BN * 128)>>>(
      tmA1, tmB1, DM, gH, FF);
  gemm_kernel<G2_BN, G2_STAGES, 1><<<dim3(DM / G2_BN, S_LEN / 128), 384, G2_STAGES * (16384 + G2_BN * 128)>>>(
      tmA2, tmB2, FF, (__nv_bfloat16*)d_out, DM);
}
```

```cpp
#include <cuda_runtime.h>
#include <cuda_bf16.h>
#include <cuda.h>
#include <stdint.h>

constexpr int S_LEN = 2048;
constexpr int DM    = 512;
constexpr int FF    = 1792;

__device__ __nv_bfloat16 g_yt[S_LEN * DM];
__device__ __nv_bfloat16 g_mod[6 * DM];
__device__ __nv_bfloat16 g_x1[S_LEN * DM];
__device__ __nv_bfloat16 g_h2[S_LEN * DM];
__device__ __nv_bfloat16 g_H[S_LEN * FF];

__device__ __forceinline__ float rbf(float x) { return __bfloat162float(__float2bfloat16_rn(x)); }
__device__ __forceinline__ float bf_lo(uint32_t u) { return __uint_as_float(u << 16); }
__device__ __forceinline__ float bf_hi(uint32_t u) { return __uint_as_float(u & 0xffff0000u); }
__device__ __forceinline__ uint32_t pack_bf(float lo, float hi) {
  uint32_t r;
  asm("cvt.rn.bf16x2.f32 %0, %1, %2;" : "=r"(r) : "f"(hi), "f"(lo));
  return r;
}
__device__ __forceinline__ uint32_t smem_u32(const void* p) { return (uint32_t)__cvta_generic_to_shared(p); }

__device__ __forceinline__ void wgmma_fence() { asm volatile("wgmma.fence.sync.aligned;\n" ::: "memory"); }
__device__ __forceinline__ void wgmma_commit() { asm volatile("wgmma.commit_group.sync.aligned;\n" ::: "memory"); }
template <int N> __device__ __forceinline__ void wgmma_wait() {
  asm volatile("wgmma.wait_group.sync.aligned %0;\n" ::"n"(N) : "memory");
}
__device__ __forceinline__ void fence_proxy_async() { asm volatile("fence.proxy.async.shared::cta;\n" ::: "memory"); }

__device__ __forceinline__ uint64_t make_desc(uint32_t saddr, uint32_t lbo_bytes, uint32_t sbo_bytes, uint32_t layout) {
  uint64_t d = 0;
  d |= (uint64_t)((saddr & 0x3FFFF) >> 4);
  d |= (uint64_t)((lbo_bytes >> 4) & 0x3FFF) << 16;
  d |= (uint64_t)((sbo_bytes >> 4) & 0x3FFF) << 32;
  d |= (uint64_t)layout << 62;
  return d;
}

__device__ __forceinline__ uint32_t bmul2(uint32_t a, uint32_t b) {
  uint32_t r; asm("mul.rn.bf16x2 %0, %1, %2;" : "=r"(r) : "r"(a), "r"(b)); return r; }
__device__ __forceinline__ uint32_t badd2(uint32_t a, uint32_t b) {
  uint32_t r; asm("add.rn.bf16x2 %0, %1, %2;" : "=r"(r) : "r"(a), "r"(b)); return r; }
__device__ __forceinline__ uint32_t bsub2(uint32_t a, uint32_t b) {
  uint32_t r; asm("sub.rn.bf16x2 %0, %1, %2;" : "=r"(r) : "r"(a), "r"(b)); return r; }
__device__ __forceinline__ uint32_t prmt(uint32_t a, uint32_t b, uint32_t sel) {
  uint32_t r; asm("prmt.b32 %0, %1, %2, %3;" : "=r"(r) : "r"(a), "r"(b), "r"(sel)); return r; }
__device__ __forceinline__ float fast_silu(float x) {
  float e, r;
  asm("ex2.approx.ftz.f32 %0, %1;" : "=f"(e) : "f"(x * -1.4426950408889634f));
  asm("rcp.approx.ftz.f32 %0, %1;" : "=f"(r) : "f"(1.0f + e));
  return x * r;
}
__device__ __forceinline__ void pdl_wait() { asm volatile("griddepcontrol.wait;" ::: "memory"); }
__device__ __forceinline__ void pdl_launch() { asm volatile("griddepcontrol.launch_dependents;" ::: "memory"); }

template<int N> __device__ __forceinline__ void wgmma_rs(float* d, uint32_t a0, uint32_t a1, uint32_t a2, uint32_t a3, uint64_t descB, int scaleD);
template<> __device__ __forceinline__ void wgmma_rs<8>(float* d, uint32_t a0, uint32_t a1, uint32_t a2, uint32_t a3, uint64_t descB, int scaleD) {
  asm volatile("{\n.reg .pred p;\nsetp.ne.b32 p, %9, 0;\n"
    "wgmma.mma_async.sync.aligned.m64n8k16.f32.bf16.bf16 {%0, %1, %2, %3}, {%4, %5, %6, %7}, %8, p, 1, 1, 0;\n}\n"
    : "+f"(d[0]), "+f"(d[1]), "+f"(d[2]), "+f"(d[3])
    : "r"(a0), "r"(a1), "r"(a2), "r"(a3), "l"(descB), "r"(scaleD));
}
template<> __device__ __forceinline__ void wgmma_rs<16>(float* d, uint32_t a0, uint32_t a1, uint32_t a2, uint32_t a3, uint64_t descB, int scaleD) {
  asm volatile("{\n.reg .pred p;\nsetp.ne.b32 p, %13, 0;\n"
    "wgmma.mma_async.sync.aligned.m64n16k16.f32.bf16.bf16 {%0, %1, %2, %3, %4, %5, %6, %7}, {%8, %9, %10, %11}, %12, p, 1, 1, 0;\n}\n"
    : "+f"(d[0]), "+f"(d[1]), "+f"(d[2]), "+f"(d[3]), "+f"(d[4]), "+f"(d[5]), "+f"(d[6]), "+f"(d[7])
    : "r"(a0), "r"(a1), "r"(a2), "r"(a3), "l"(descB), "r"(scaleD));
}
template<> __device__ __forceinline__ void wgmma_rs<24>(float* d, uint32_t a0, uint32_t a1, uint32_t a2, uint32_t a3, uint64_t descB, int scaleD) {
  asm volatile("{\n.reg .pred p;\nsetp.ne.b32 p, %17, 0;\n"
    "wgmma.mma_async.sync.aligned.m64n24k16.f32.bf16.bf16 {%0, %1, %2, %3, %4, %5, %6, %7, %8, %9, %10, %11}, {%12, %13, %14, %15}, %16, p, 1, 1, 0;\n}\n"
    : "+f"(d[0]), "+f"(d[1]), "+f"(d[2]), "+f"(d[3]), "+f"(d[4]), "+f"(d[5]), "+f"(d[6]), "+f"(d[7]), "+f"(d[8]), "+f"(d[9]), "+f"(d[10]), "+f"(d[11])
    : "r"(a0), "r"(a1), "r"(a2), "r"(a3), "l"(descB), "r"(scaleD));
}
template<> __device__ __forceinline__ void wgmma_rs<32>(float* d, uint32_t a0, uint32_t a1, uint32_t a2, uint32_t a3, uint64_t descB, int scaleD) {
  asm volatile("{\n.reg .pred p;\nsetp.ne.b32 p, %21, 0;\n"
    "wgmma.mma_async.sync.aligned.m64n32k16.f32.bf16.bf16 {%0, %1, %2, %3, %4, %5, %6, %7, %8, %9, %10, %11, %12, %13, %14, %15}, {%16, %17, %18, %19}, %20, p, 1, 1, 0;\n}\n"
    : "+f"(d[0]), "+f"(d[1]), "+f"(d[2]), "+f"(d[3]), "+f"(d[4]), "+f"(d[5]), "+f"(d[6]), "+f"(d[7]), "+f"(d[8]), "+f"(d[9]), "+f"(d[10]), "+f"(d[11]), "+f"(d[12]), "+f"(d[13]), "+f"(d[14]), "+f"(d[15])
    : "r"(a0), "r"(a1), "r"(a2), "r"(a3), "l"(descB), "r"(scaleD));
}
template<> __device__ __forceinline__ void wgmma_rs<40>(float* d, uint32_t a0, uint32_t a1, uint32_t a2, uint32_t a3, uint64_t descB, int scaleD) {
  asm volatile("{\n.reg .pred p;\nsetp.ne.b32 p, %25, 0;\n"
    "wgmma.mma_async.sync.aligned.m64n40k16.f32.bf16.bf16 {%0, %1, %2, %3, %4, %5, %6, %7, %8, %9, %10, %11, %12, %13, %14, %15, %16, %17, %18, %19}, {%20, %21, %22, %23}, %24, p, 1, 1, 0;\n}\n"
    : "+f"(d[0]), "+f"(d[1]), "+f"(d[2]), "+f"(d[3]), "+f"(d[4]), "+f"(d[5]), "+f"(d[6]), "+f"(d[7]), "+f"(d[8]), "+f"(d[9]), "+f"(d[10]), "+f"(d[11]), "+f"(d[12]), "+f"(d[13]), "+f"(d[14]), "+f"(d[15]), "+f"(d[16]), "+f"(d[17]), "+f"(d[18]), "+f"(d[19])
    : "r"(a0), "r"(a1), "r"(a2), "r"(a3), "l"(descB), "r"(scaleD));
}
template<> __device__ __forceinline__ void wgmma_rs<48>(float* d, uint32_t a0, uint32_t a1, uint32_t a2, uint32_t a3, uint64_t descB, int scaleD) {
  asm volatile("{\n.reg .pred p;\nsetp.ne.b32 p, %29, 0;\n"
    "wgmma.mma_async.sync.aligned.m64n48k16.f32.bf16.bf16 {%0, %1, %2, %3, %4, %5, %6, %7, %8, %9, %10, %11, %12, %13, %14, %15, %16, %17, %18, %19, %20, %21, %22, %23}, {%24, %25, %26, %27}, %28, p, 1, 1, 0;\n}\n"
    : "+f"(d[0]), "+f"(d[1]), "+f"(d[2]), "+f"(d[3]), "+f"(d[4]), "+f"(d[5]), "+f"(d[6]), "+f"(d[7]), "+f"(d[8]), "+f"(d[9]), "+f"(d[10]), "+f"(d[11]), "+f"(d[12]), "+f"(d[13]), "+f"(d[14]), "+f"(d[15]), "+f"(d[16]), "+f"(d[17]), "+f"(d[18]), "+f"(d[19]), "+f"(d[20]), "+f"(d[21]), "+f"(d[22]), "+f"(d[23])
    : "r"(a0), "r"(a1), "r"(a2), "r"(a3), "l"(descB), "r"(scaleD));
}
template<> __device__ __forceinline__ void wgmma_rs<56>(float* d, uint32_t a0, uint32_t a1, uint32_t a2, uint32_t a3, uint64_t descB, int scaleD) {
  asm volatile("{\n.reg .pred p;\nsetp.ne.b32 p, %33, 0;\n"
    "wgmma.mma_async.sync.aligned.m64n56k16.f32.bf16.bf16 {%0, %1, %2, %3, %4, %5, %6, %7, %8, %9, %10, %11, %12, %13, %14, %15, %16, %17, %18, %19, %20, %21, %22, %23, %24, %25, %26, %27}, {%28, %29, %30, %31}, %32, p, 1, 1, 0;\n}\n"
    : "+f"(d[0]), "+f"(d[1]), "+f"(d[2]), "+f"(d[3]), "+f"(d[4]), "+f"(d[5]), "+f"(d[6]), "+f"(d[7]), "+f"(d[8]), "+f"(d[9]), "+f"(d[10]), "+f"(d[11]), "+f"(d[12]), "+f"(d[13]), "+f"(d[14]), "+f"(d[15]), "+f"(d[16]), "+f"(d[17]), "+f"(d[18]), "+f"(d[19]), "+f"(d[20]), "+f"(d[21]), "+f"(d[22]), "+f"(d[23]), "+f"(d[24]), "+f"(d[25]), "+f"(d[26]), "+f"(d[27])
    : "r"(a0), "r"(a1), "r"(a2), "r"(a3), "l"(descB), "r"(scaleD));
}
template<> __device__ __forceinline__ void wgmma_rs<64>(float* d, uint32_t a0, uint32_t a1, uint32_t a2, uint32_t a3, uint64_t descB, int scaleD) {
  asm volatile("{\n.reg .pred p;\nsetp.ne.b32 p, %37, 0;\n"
    "wgmma.mma_async.sync.aligned.m64n64k16.f32.bf16.bf16 {%0, %1, %2, %3, %4, %5, %6, %7, %8, %9, %10, %11, %12, %13, %14, %15, %16, %17, %18, %19, %20, %21, %22, %23, %24, %25, %26, %27, %28, %29, %30, %31}, {%32, %33, %34, %35}, %36, p, 1, 1, 0;\n}\n"
    : "+f"(d[0]), "+f"(d[1]), "+f"(d[2]), "+f"(d[3]), "+f"(d[4]), "+f"(d[5]), "+f"(d[6]), "+f"(d[7]), "+f"(d[8]), "+f"(d[9]), "+f"(d[10]), "+f"(d[11]), "+f"(d[12]), "+f"(d[13]), "+f"(d[14]), "+f"(d[15]), "+f"(d[16]), "+f"(d[17]), "+f"(d[18]), "+f"(d[19]), "+f"(d[20]), "+f"(d[21]), "+f"(d[22]), "+f"(d[23]), "+f"(d[24]), "+f"(d[25]), "+f"(d[26]), "+f"(d[27]), "+f"(d[28]), "+f"(d[29]), "+f"(d[30]), "+f"(d[31])
    : "r"(a0), "r"(a1), "r"(a2), "r"(a3), "l"(descB), "r"(scaleD));
}
template<> __device__ __forceinline__ void wgmma_rs<72>(float* d, uint32_t a0, uint32_t a1, uint32_t a2, uint32_t a3, uint64_t descB, int scaleD) {
  asm volatile("{\n.reg .pred p;\nsetp.ne.b32 p, %41, 0;\n"
    "wgmma.mma_async.sync.aligned.m64n72k16.f32.bf16.bf16 {%0, %1, %2, %3, %4, %5, %6, %7, %8, %9, %10, %11, %12, %13, %14, %15, %16, %17, %18, %19, %20, %21, %22, %23, %24, %25, %26, %27, %28, %29, %30, %31, %32, %33, %34, %35}, {%36, %37, %38, %39}, %40, p, 1, 1, 0;\n}\n"
    : "+f"(d[0]), "+f"(d[1]), "+f"(d[2]), "+f"(d[3]), "+f"(d[4]), "+f"(d[5]), "+f"(d[6]), "+f"(d[7]), "+f"(d[8]), "+f"(d[9]), "+f"(d[10]), "+f"(d[11]), "+f"(d[12]), "+f"(d[13]), "+f"(d[14]), "+f"(d[15]), "+f"(d[16]), "+f"(d[17]), "+f"(d[18]), "+f"(d[19]), "+f"(d[20]), "+f"(d[21]), "+f"(d[22]), "+f"(d[23]), "+f"(d[24]), "+f"(d[25]), "+f"(d[26]), "+f"(d[27]), "+f"(d[28]), "+f"(d[29]), "+f"(d[30]), "+f"(d[31]), "+f"(d[32]), "+f"(d[33]), "+f"(d[34]), "+f"(d[35])
    : "r"(a0), "r"(a1), "r"(a2), "r"(a3), "l"(descB), "r"(scaleD));
}
template<> __device__ __forceinline__ void wgmma_rs<80>(float* d, uint32_t a0, uint32_t a1, uint32_t a2, uint32_t a3, uint64_t descB, int scaleD) {
  asm volatile("{\n.reg .pred p;\nsetp.ne.b32 p, %45, 0;\n"
    "wgmma.mma_async.sync.aligned.m64n80k16.f32.bf16.bf16 {%0, %1, %2, %3, %4, %5, %6, %7, %8, %9, %10, %11, %12, %13, %14, %15, %16, %17, %18, %19, %20, %21, %22, %23, %24, %25, %26, %27, %28, %29, %30, %31, %32, %33, %34, %35, %36, %37, %38, %39}, {%40, %41, %42, %43}, %44, p, 1, 1, 0;\n}\n"
    : "+f"(d[0]), "+f"(d[1]), "+f"(d[2]), "+f"(d[3]), "+f"(d[4]), "+f"(d[5]), "+f"(d[6]), "+f"(d[7]), "+f"(d[8]), "+f"(d[9]), "+f"(d[10]), "+f"(d[11]), "+f"(d[12]), "+f"(d[13]), "+f"(d[14]), "+f"(d[15]), "+f"(d[16]), "+f"(d[17]), "+f"(d[18]), "+f"(d[19]), "+f"(d[20]), "+f"(d[21]), "+f"(d[22]), "+f"(d[23]), "+f"(d[24]), "+f"(d[25]), "+f"(d[26]), "+f"(d[27]), "+f"(d[28]), "+f"(d[29]), "+f"(d[30]), "+f"(d[31]), "+f"(d[32]), "+f"(d[33]), "+f"(d[34]), "+f"(d[35]), "+f"(d[36]), "+f"(d[37]), "+f"(d[38]), "+f"(d[39])
    : "r"(a0), "r"(a1), "r"(a2), "r"(a3), "l"(descB), "r"(scaleD));
}
template<> __device__ __forceinline__ void wgmma_rs<88>(float* d, uint32_t a0, uint32_t a1, uint32_t a2, uint32_t a3, uint64_t descB, int scaleD) {
  asm volatile("{\n.reg .pred p;\nsetp.ne.b32 p, %49, 0;\n"
    "wgmma.mma_async.sync.aligned.m64n88k16.f32.bf16.bf16 {%0, %1, %2, %3, %4, %5, %6, %7, %8, %9, %10, %11, %12, %13, %14, %15, %16, %17, %18, %19, %20, %21, %22, %23, %24, %25, %26, %27, %28, %29, %30, %31, %32, %33, %34, %35, %36, %37, %38, %39, %40, %41, %42, %43}, {%44, %45, %46, %47}, %48, p, 1, 1, 0;\n}\n"
    : "+f"(d[0]), "+f"(d[1]), "+f"(d[2]), "+f"(d[3]), "+f"(d[4]), "+f"(d[5]), "+f"(d[6]), "+f"(d[7]), "+f"(d[8]), "+f"(d[9]), "+f"(d[10]), "+f"(d[11]), "+f"(d[12]), "+f"(d[13]), "+f"(d[14]), "+f"(d[15]), "+f"(d[16]), "+f"(d[17]), "+f"(d[18]), "+f"(d[19]), "+f"(d[20]), "+f"(d[21]), "+f"(d[22]), "+f"(d[23]), "+f"(d[24]), "+f"(d[25]), "+f"(d[26]), "+f"(d[27]), "+f"(d[28]), "+f"(d[29]), "+f"(d[30]), "+f"(d[31]), "+f"(d[32]), "+f"(d[33]), "+f"(d[34]), "+f"(d[35]), "+f"(d[36]), "+f"(d[37]), "+f"(d[38]), "+f"(d[39]), "+f"(d[40]), "+f"(d[41]), "+f"(d[42]), "+f"(d[43])
    : "r"(a0), "r"(a1), "r"(a2), "r"(a3), "l"(descB), "r"(scaleD));
}
template<> __device__ __forceinline__ void wgmma_rs<96>(float* d, uint32_t a0, uint32_t a1, uint32_t a2, uint32_t a3, uint64_t descB, int scaleD) {
  asm volatile("{\n.reg .pred p;\nsetp.ne.b32 p, %53, 0;\n"
    "wgmma.mma_async.sync.aligned.m64n96k16.f32.bf16.bf16 {%0, %1, %2, %3, %4, %5, %6, %7, %8, %9, %10, %11, %12, %13, %14, %15, %16, %17, %18, %19, %20, %21, %22, %23, %24, %25, %26, %27, %28, %29, %30, %31, %32, %33, %34, %35, %36, %37, %38, %39, %40, %41, %42, %43, %44, %45, %46, %47}, {%48, %49, %50, %51}, %52, p, 1, 1, 0;\n}\n"
    : "+f"(d[0]), "+f"(d[1]), "+f"(d[2]), "+f"(d[3]), "+f"(d[4]), "+f"(d[5]), "+f"(d[6]), "+f"(d[7]), "+f"(d[8]), "+f"(d[9]), "+f"(d[10]), "+f"(d[11]), "+f"(d[12]), "+f"(d[13]), "+f"(d[14]), "+f"(d[15]), "+f"(d[16]), "+f"(d[17]), "+f"(d[18]), "+f"(d[19]), "+f"(d[20]), "+f"(d[21]), "+f"(d[22]), "+f"(d[23]), "+f"(d[24]), "+f"(d[25]), "+f"(d[26]), "+f"(d[27]), "+f"(d[28]), "+f"(d[29]), "+f"(d[30]), "+f"(d[31]), "+f"(d[32]), "+f"(d[33]), "+f"(d[34]), "+f"(d[35]), "+f"(d[36]), "+f"(d[37]), "+f"(d[38]), "+f"(d[39]), "+f"(d[40]), "+f"(d[41]), "+f"(d[42]), "+f"(d[43]), "+f"(d[44]), "+f"(d[45]), "+f"(d[46]), "+f"(d[47])
    : "r"(a0), "r"(a1), "r"(a2), "r"(a3), "l"(descB), "r"(scaleD));
}
template<> __device__ __forceinline__ void wgmma_rs<104>(float* d, uint32_t a0, uint32_t a1, uint32_t a2, uint32_t a3, uint64_t descB, int scaleD) {
  asm volatile("{\n.reg .pred p;\nsetp.ne.b32 p, %57, 0;\n"
    "wgmma.mma_async.sync.aligned.m64n104k16.f32.bf16.bf16 {%0, %1, %2, %3, %4, %5, %6, %7, %8, %9, %10, %11, %12, %13, %14, %15, %16, %17, %18, %19, %20, %21, %22, %23, %24, %25, %26, %27, %28, %29, %30, %31, %32, %33, %34, %35, %36, %37, %38, %39, %40, %41, %42, %43, %44, %45, %46, %47, %48, %49, %50, %51}, {%52, %53, %54, %55}, %56, p, 1, 1, 0;\n}\n"
    : "+f"(d[0]), "+f"(d[1]), "+f"(d[2]), "+f"(d[3]), "+f"(d[4]), "+f"(d[5]), "+f"(d[6]), "+f"(d[7]), "+f"(d[8]), "+f"(d[9]), "+f"(d[10]), "+f"(d[11]), "+f"(d[12]), "+f"(d[13]), "+f"(d[14]), "+f"(d[15]), "+f"(d[16]), "+f"(d[17]), "+f"(d[18]), "+f"(d[19]), "+f"(d[20]), "+f"(d[21]), "+f"(d[22]), "+f"(d[23]), "+f"(d[24]), "+f"(d[25]), "+f"(d[26]), "+f"(d[27]), "+f"(d[28]), "+f"(d[29]), "+f"(d[30]), "+f"(d[31]), "+f"(d[32]), "+f"(d[33]), "+f"(d[34]), "+f"(d[35]), "+f"(d[36]), "+f"(d[37]), "+f"(d[38]), "+f"(d[39]), "+f"(d[40]), "+f"(d[41]), "+f"(d[42]), "+f"(d[43]), "+f"(d[44]), "+f"(d[45]), "+f"(d[46]), "+f"(d[47]), "+f"(d[48]), "+f"(d[49]), "+f"(d[50]), "+f"(d[51])
    : "r"(a0), "r"(a1), "r"(a2), "r"(a3), "l"(descB), "r"(scaleD));
}
template<> __device__ __forceinline__ void wgmma_rs<112>(float* d, uint32_t a0, uint32_t a1, uint32_t a2, uint32_t a3, uint64_t descB, int scaleD) {
  asm volatile("{\n.reg .pred p;\nsetp.ne.b32 p, %61, 0;\n"
    "wgmma.mma_async.sync.aligned.m64n112k16.f32.bf16.bf16 {%0, %1, %2, %3, %4, %5, %6, %7, %8, %9, %10, %11, %12, %13, %14, %15, %16, %17, %18, %19, %20, %21, %22, %23, %24, %25, %26, %27, %28, %29, %30, %31, %32, %33, %34, %35, %36, %37, %38, %39, %40, %41, %42, %43, %44, %45, %46, %47, %48, %49, %50, %51, %52, %53, %54, %55}, {%56, %57, %58, %59}, %60, p, 1, 1, 0;\n}\n"
    : "+f"(d[0]), "+f"(d[1]), "+f"(d[2]), "+f"(d[3]), "+f"(d[4]), "+f"(d[5]), "+f"(d[6]), "+f"(d[7]), "+f"(d[8]), "+f"(d[9]), "+f"(d[10]), "+f"(d[11]), "+f"(d[12]), "+f"(d[13]), "+f"(d[14]), "+f"(d[15]), "+f"(d[16]), "+f"(d[17]), "+f"(d[18]), "+f"(d[19]), "+f"(d[20]), "+f"(d[21]), "+f"(d[22]), "+f"(d[23]), "+f"(d[24]), "+f"(d[25]), "+f"(d[26]), "+f"(d[27]), "+f"(d[28]), "+f"(d[29]), "+f"(d[30]), "+f"(d[31]), "+f"(d[32]), "+f"(d[33]), "+f"(d[34]), "+f"(d[35]), "+f"(d[36]), "+f"(d[37]), "+f"(d[38]), "+f"(d[39]), "+f"(d[40]), "+f"(d[41]), "+f"(d[42]), "+f"(d[43]), "+f"(d[44]), "+f"(d[45]), "+f"(d[46]), "+f"(d[47]), "+f"(d[48]), "+f"(d[49]), "+f"(d[50]), "+f"(d[51]), "+f"(d[52]), "+f"(d[53]), "+f"(d[54]), "+f"(d[55])
    : "r"(a0), "r"(a1), "r"(a2), "r"(a3), "l"(descB), "r"(scaleD));
}
template<> __device__ __forceinline__ void wgmma_rs<120>(float* d, uint32_t a0, uint32_t a1, uint32_t a2, uint32_t a3, uint64_t descB, int scaleD) {
  asm volatile("{\n.reg .pred p;\nsetp.ne.b32 p, %65, 0;\n"
    "wgmma.mma_async.sync.aligned.m64n120k16.f32.bf16.bf16 {%0, %1, %2, %3, %4, %5, %6, %7, %8, %9, %10, %11, %12, %13, %14, %15, %16, %17, %18, %19, %20, %21, %22, %23, %24, %25, %26, %27, %28, %29, %30, %31, %32, %33, %34, %35, %36, %37, %38, %39, %40, %41, %42, %43, %44, %45, %46, %47, %48, %49, %50, %51, %52, %53, %54, %55, %56, %57, %58, %59}, {%60, %61, %62, %63}, %64, p, 1, 1, 0;\n}\n"
    : "+f"(d[0]), "+f"(d[1]), "+f"(d[2]), "+f"(d[3]), "+f"(d[4]), "+f"(d[5]), "+f"(d[6]), "+f"(d[7]), "+f"(d[8]), "+f"(d[9]), "+f"(d[10]), "+f"(d[11]), "+f"(d[12]), "+f"(d[13]), "+f"(d[14]), "+f"(d[15]), "+f"(d[16]), "+f"(d[17]), "+f"(d[18]), "+f"(d[19]), "+f"(d[20]), "+f"(d[21]), "+f"(d[22]), "+f"(d[23]), "+f"(d[24]), "+f"(d[25]), "+f"(d[26]), "+f"(d[27]), "+f"(d[28]), "+f"(d[29]), "+f"(d[30]), "+f"(d[31]), "+f"(d[32]), "+f"(d[33]), "+f"(d[34]), "+f"(d[35]), "+f"(d[36]), "+f"(d[37]), "+f"(d[38]), "+f"(d[39]), "+f"(d[40]), "+f"(d[41]), "+f"(d[42]), "+f"(d[43]), "+f"(d[44]), "+f"(d[45]), "+f"(d[46]), "+f"(d[47]), "+f"(d[48]), "+f"(d[49]), "+f"(d[50]), "+f"(d[51]), "+f"(d[52]), "+f"(d[53]), "+f"(d[54]), "+f"(d[55]), "+f"(d[56]), "+f"(d[57]), "+f"(d[58]), "+f"(d[59])
    : "r"(a0), "r"(a1), "r"(a2), "r"(a3), "l"(descB), "r"(scaleD));
}
template<> __device__ __forceinline__ void wgmma_rs<128>(float* d, uint32_t a0, uint32_t a1, uint32_t a2, uint32_t a3, uint64_t descB, int scaleD) {
  asm volatile("{\n.reg .pred p;\nsetp.ne.b32 p, %69, 0;\n"
    "wgmma.mma_async.sync.aligned.m64n128k16.f32.bf16.bf16 {%0, %1, %2, %3, %4, %5, %6, %7, %8, %9, %10, %11, %12, %13, %14, %15, %16, %17, %18, %19, %20, %21, %22, %23, %24, %25, %26, %27, %28, %29, %30, %31, %32, %33, %34, %35, %36, %37, %38, %39, %40, %41, %42, %43, %44, %45, %46, %47, %48, %49, %50, %51, %52, %53, %54, %55, %56, %57, %58, %59, %60, %61, %62, %63}, {%64, %65, %66, %67}, %68, p, 1, 1, 0;\n}\n"
    : "+f"(d[0]), "+f"(d[1]), "+f"(d[2]), "+f"(d[3]), "+f"(d[4]), "+f"(d[5]), "+f"(d[6]), "+f"(d[7]), "+f"(d[8]), "+f"(d[9]), "+f"(d[10]), "+f"(d[11]), "+f"(d[12]), "+f"(d[13]), "+f"(d[14]), "+f"(d[15]), "+f"(d[16]), "+f"(d[17]), "+f"(d[18]), "+f"(d[19]), "+f"(d[20]), "+f"(d[21]), "+f"(d[22]), "+f"(d[23]), "+f"(d[24]), "+f"(d[25]), "+f"(d[26]), "+f"(d[27]), "+f"(d[28]), "+f"(d[29]), "+f"(d[30]), "+f"(d[31]), "+f"(d[32]), "+f"(d[33]), "+f"(d[34]), "+f"(d[35]), "+f"(d[36]), "+f"(d[37]), "+f"(d[38]), "+f"(d[39]), "+f"(d[40]), "+f"(d[41]), "+f"(d[42]), "+f"(d[43]), "+f"(d[44]), "+f"(d[45]), "+f"(d[46]), "+f"(d[47]), "+f"(d[48]), "+f"(d[49]), "+f"(d[50]), "+f"(d[51]), "+f"(d[52]), "+f"(d[53]), "+f"(d[54]), "+f"(d[55]), "+f"(d[56]), "+f"(d[57]), "+f"(d[58]), "+f"(d[59]), "+f"(d[60]), "+f"(d[61]), "+f"(d[62]), "+f"(d[63])
    : "r"(a0), "r"(a1), "r"(a2), "r"(a3), "l"(descB), "r"(scaleD));
}
template<int N> __device__ __forceinline__ void wgmma_ss(float* d, uint64_t descA, uint64_t descB, int scaleD);
template<> __device__ __forceinline__ void wgmma_ss<64>(float* d, uint64_t descA, uint64_t descB, int scaleD) {
  asm volatile("{\n.reg .pred p;\nsetp.ne.b32 p, %34, 0;\n"
    "wgmma.mma_async.sync.aligned.m64n64k16.f32.bf16.bf16 {%0, %1, %2, %3, %4, %5, %6, %7, %8, %9, %10, %11, %12, %13, %14, %15, %16, %17, %18, %19, %20, %21, %22, %23, %24, %25, %26, %27, %28, %29, %30, %31}, %32, %33, p, 1, 1, 0, 1;\n}\n"
    : "+f"(d[0]), "+f"(d[1]), "+f"(d[2]), "+f"(d[3]), "+f"(d[4]), "+f"(d[5]), "+f"(d[6]), "+f"(d[7]), "+f"(d[8]), "+f"(d[9]), "+f"(d[10]), "+f"(d[11]), "+f"(d[12]), "+f"(d[13]), "+f"(d[14]), "+f"(d[15]), "+f"(d[16]), "+f"(d[17]), "+f"(d[18]), "+f"(d[19]), "+f"(d[20]), "+f"(d[21]), "+f"(d[22]), "+f"(d[23]), "+f"(d[24]), "+f"(d[25]), "+f"(d[26]), "+f"(d[27]), "+f"(d[28]), "+f"(d[29]), "+f"(d[30]), "+f"(d[31])
    : "l"(descA), "l"(descB), "r"(scaleD));
}
template<> __device__ __forceinline__ void wgmma_ss<128>(float* d, uint64_t descA, uint64_t descB, int scaleD) {
  asm volatile("{\n.reg .pred p;\nsetp.ne.b32 p, %66, 0;\n"
    "wgmma.mma_async.sync.aligned.m64n128k16.f32.bf16.bf16 {%0, %1, %2, %3, %4, %5, %6, %7, %8, %9, %10, %11, %12, %13, %14, %15, %16, %17, %18, %19, %20, %21, %22, %23, %24, %25, %26, %27, %28, %29, %30, %31, %32, %33, %34, %35, %36, %37, %38, %39, %40, %41, %42, %43, %44, %45, %46, %47, %48, %49, %50, %51, %52, %53, %54, %55, %56, %57, %58, %59, %60, %61, %62, %63}, %64, %65, p, 1, 1, 0, 1;\n}\n"
    : "+f"(d[0]), "+f"(d[1]), "+f"(d[2]), "+f"(d[3]), "+f"(d[4]), "+f"(d[5]), "+f"(d[6]), "+f"(d[7]), "+f"(d[8]), "+f"(d[9]), "+f"(d[10]), "+f"(d[11]), "+f"(d[12]), "+f"(d[13]), "+f"(d[14]), "+f"(d[15]), "+f"(d[16]), "+f"(d[17]), "+f"(d[18]), "+f"(d[19]), "+f"(d[20]), "+f"(d[21]), "+f"(d[22]), "+f"(d[23]), "+f"(d[24]), "+f"(d[25]), "+f"(d[26]), "+f"(d[27]), "+f"(d[28]), "+f"(d[29]), "+f"(d[30]), "+f"(d[31]), "+f"(d[32]), "+f"(d[33]), "+f"(d[34]), "+f"(d[35]), "+f"(d[36]), "+f"(d[37]), "+f"(d[38]), "+f"(d[39]), "+f"(d[40]), "+f"(d[41]), "+f"(d[42]), "+f"(d[43]), "+f"(d[44]), "+f"(d[45]), "+f"(d[46]), "+f"(d[47]), "+f"(d[48]), "+f"(d[49]), "+f"(d[50]), "+f"(d[51]), "+f"(d[52]), "+f"(d[53]), "+f"(d[54]), "+f"(d[55]), "+f"(d[56]), "+f"(d[57]), "+f"(d[58]), "+f"(d[59]), "+f"(d[60]), "+f"(d[61]), "+f"(d[62]), "+f"(d[63])
    : "l"(descA), "l"(descB), "r"(scaleD));
}
template<> __device__ __forceinline__ void wgmma_ss<224>(float* d, uint64_t descA, uint64_t descB, int scaleD) {
  asm volatile("{\n.reg .pred p;\nsetp.ne.b32 p, %114, 0;\n"
    "wgmma.mma_async.sync.aligned.m64n224k16.f32.bf16.bf16 {%0, %1, %2, %3, %4, %5, %6, %7, %8, %9, %10, %11, %12, %13, %14, %15, %16, %17, %18, %19, %20, %21, %22, %23, %24, %25, %26, %27, %28, %29, %30, %31, %32, %33, %34, %35, %36, %37, %38, %39, %40, %41, %42, %43, %44, %45, %46, %47, %48, %49, %50, %51, %52, %53, %54, %55, %56, %57, %58, %59, %60, %61, %62, %63, %64, %65, %66, %67, %68, %69, %70, %71, %72, %73, %74, %75, %76, %77, %78, %79, %80, %81, %82, %83, %84, %85, %86, %87, %88, %89, %90, %91, %92, %93, %94, %95, %96, %97, %98, %99, %100, %101, %102, %103, %104, %105, %106, %107, %108, %109, %110, %111}, %112, %113, p, 1, 1, 0, 1;\n}\n"
    : "+f"(d[0]), "+f"(d[1]), "+f"(d[2]), "+f"(d[3]), "+f"(d[4]), "+f"(d[5]), "+f"(d[6]), "+f"(d[7]), "+f"(d[8]), "+f"(d[9]), "+f"(d[10]), "+f"(d[11]), "+f"(d[12]), "+f"(d[13]), "+f"(d[14]), "+f"(d[15]), "+f"(d[16]), "+f"(d[17]), "+f"(d[18]), "+f"(d[19]), "+f"(d[20]), "+f"(d[21]), "+f"(d[22]), "+f"(d[23]), "+f"(d[24]), "+f"(d[25]), "+f"(d[26]), "+f"(d[27]), "+f"(d[28]), "+f"(d[29]), "+f"(d[30]), "+f"(d[31]), "+f"(d[32]), "+f"(d[33]), "+f"(d[34]), "+f"(d[35]), "+f"(d[36]), "+f"(d[37]), "+f"(d[38]), "+f"(d[39]), "+f"(d[40]), "+f"(d[41]), "+f"(d[42]), "+f"(d[43]), "+f"(d[44]), "+f"(d[45]), "+f"(d[46]), "+f"(d[47]), "+f"(d[48]), "+f"(d[49]), "+f"(d[50]), "+f"(d[51]), "+f"(d[52]), "+f"(d[53]), "+f"(d[54]), "+f"(d[55]), "+f"(d[56]), "+f"(d[57]), "+f"(d[58]), "+f"(d[59]), "+f"(d[60]), "+f"(d[61]), "+f"(d[62]), "+f"(d[63]), "+f"(d[64]), "+f"(d[65]), "+f"(d[66]), "+f"(d[67]), "+f"(d[68]), "+f"(d[69]), "+f"(d[70]), "+f"(d[71]), "+f"(d[72]), "+f"(d[73]), "+f"(d[74]), "+f"(d[75]), "+f"(d[76]), "+f"(d[77]), "+f"(d[78]), "+f"(d[79]), "+f"(d[80]), "+f"(d[81]), "+f"(d[82]), "+f"(d[83]), "+f"(d[84]), "+f"(d[85]), "+f"(d[86]), "+f"(d[87]), "+f"(d[88]), "+f"(d[89]), "+f"(d[90]), "+f"(d[91]), "+f"(d[92]), "+f"(d[93]), "+f"(d[94]), "+f"(d[95]), "+f"(d[96]), "+f"(d[97]), "+f"(d[98]), "+f"(d[99]), "+f"(d[100]), "+f"(d[101]), "+f"(d[102]), "+f"(d[103]), "+f"(d[104]), "+f"(d[105]), "+f"(d[106]), "+f"(d[107]), "+f"(d[108]), "+f"(d[109]), "+f"(d[110]), "+f"(d[111])
    : "l"(descA), "l"(descB), "r"(scaleD));
}
template<> __device__ __forceinline__ void wgmma_ss<256>(float* d, uint64_t descA, uint64_t descB, int scaleD) {
  asm volatile("{\n.reg .pred p;\nsetp.ne.b32 p, %130, 0;\n"
    "wgmma.mma_async.sync.aligned.m64n256k16.f32.bf16.bf16 {%0, %1, %2, %3, %4, %5, %6, %7, %8, %9, %10, %11, %12, %13, %14, %15, %16, %17, %18, %19, %20, %21, %22, %23, %24, %25, %26, %27, %28, %29, %30, %31, %32, %33, %34, %35, %36, %37, %38, %39, %40, %41, %42, %43, %44, %45, %46, %47, %48, %49, %50, %51, %52, %53, %54, %55, %56, %57, %58, %59, %60, %61, %62, %63, %64, %65, %66, %67, %68, %69, %70, %71, %72, %73, %74, %75, %76, %77, %78, %79, %80, %81, %82, %83, %84, %85, %86, %87, %88, %89, %90, %91, %92, %93, %94, %95, %96, %97, %98, %99, %100, %101, %102, %103, %104, %105, %106, %107, %108, %109, %110, %111, %112, %113, %114, %115, %116, %117, %118, %119, %120, %121, %122, %123, %124, %125, %126, %127}, %128, %129, p, 1, 1, 0, 1;\n}\n"
    : "+f"(d[0]), "+f"(d[1]), "+f"(d[2]), "+f"(d[3]), "+f"(d[4]), "+f"(d[5]), "+f"(d[6]), "+f"(d[7]), "+f"(d[8]), "+f"(d[9]), "+f"(d[10]), "+f"(d[11]), "+f"(d[12]), "+f"(d[13]), "+f"(d[14]), "+f"(d[15]), "+f"(d[16]), "+f"(d[17]), "+f"(d[18]), "+f"(d[19]), "+f"(d[20]), "+f"(d[21]), "+f"(d[22]), "+f"(d[23]), "+f"(d[24]), "+f"(d[25]), "+f"(d[26]), "+f"(d[27]), "+f"(d[28]), "+f"(d[29]), "+f"(d[30]), "+f"(d[31]), "+f"(d[32]), "+f"(d[33]), "+f"(d[34]), "+f"(d[35]), "+f"(d[36]), "+f"(d[37]), "+f"(d[38]), "+f"(d[39]), "+f"(d[40]), "+f"(d[41]), "+f"(d[42]), "+f"(d[43]), "+f"(d[44]), "+f"(d[45]), "+f"(d[46]), "+f"(d[47]), "+f"(d[48]), "+f"(d[49]), "+f"(d[50]), "+f"(d[51]), "+f"(d[52]), "+f"(d[53]), "+f"(d[54]), "+f"(d[55]), "+f"(d[56]), "+f"(d[57]), "+f"(d[58]), "+f"(d[59]), "+f"(d[60]), "+f"(d[61]), "+f"(d[62]), "+f"(d[63]), "+f"(d[64]), "+f"(d[65]), "+f"(d[66]), "+f"(d[67]), "+f"(d[68]), "+f"(d[69]), "+f"(d[70]), "+f"(d[71]), "+f"(d[72]), "+f"(d[73]), "+f"(d[74]), "+f"(d[75]), "+f"(d[76]), "+f"(d[77]), "+f"(d[78]), "+f"(d[79]), "+f"(d[80]), "+f"(d[81]), "+f"(d[82]), "+f"(d[83]), "+f"(d[84]), "+f"(d[85]), "+f"(d[86]), "+f"(d[87]), "+f"(d[88]), "+f"(d[89]), "+f"(d[90]), "+f"(d[91]), "+f"(d[92]), "+f"(d[93]), "+f"(d[94]), "+f"(d[95]), "+f"(d[96]), "+f"(d[97]), "+f"(d[98]), "+f"(d[99]), "+f"(d[100]), "+f"(d[101]), "+f"(d[102]), "+f"(d[103]), "+f"(d[104]), "+f"(d[105]), "+f"(d[106]), "+f"(d[107]), "+f"(d[108]), "+f"(d[109]), "+f"(d[110]), "+f"(d[111]), "+f"(d[112]), "+f"(d[113]), "+f"(d[114]), "+f"(d[115]), "+f"(d[116]), "+f"(d[117]), "+f"(d[118]), "+f"(d[119]), "+f"(d[120]), "+f"(d[121]), "+f"(d[122]), "+f"(d[123]), "+f"(d[124]), "+f"(d[125]), "+f"(d[126]), "+f"(d[127])
    : "l"(descA), "l"(descB), "r"(scaleD));
}


constexpr int K1_THREADS = 512;
constexpr int U_ROWS  = 136;
constexpr int U_PLANE = U_ROWS * 16;
constexpr int U_CH    = 2 * U_PLANE;
constexpr int F_LEN   = 2048 + 32;
constexpr int F_COPY  = F_LEN * 2;
constexpr int F_CH    = 2 * F_COPY;
constexpr int P_CH    = 4 * 2048 * 4;
constexpr int K1_OFF_U = 0;
constexpr int K1_OFF_F = K1_OFF_U + 4 * U_CH;
constexpr int K1_OFF_P = K1_OFF_F + 4 * F_CH;
constexpr int K1_OFF_R = K1_OFF_P + 4 * P_CH;
constexpr int K1_SMEM  = K1_OFF_R + 8 * 32 * 4;

template <int T> struct ConvStep {
  static __device__ __forceinline__ void run(float* acc, const uint32_t* fp, uint64_t d0, uint64_t d1) {
    constexpr int N = 128 - 8 * T;
    uint32_t a0 = fp[64 * T], a1 = fp[64 * T + 4], a3 = fp[64 * T + 8];
    uint32_t b0 = fp[64 * T + 32], b1 = fp[64 * T + 36], b3 = fp[64 * T + 40];
    wgmma_fence();
    wgmma_rs<N>(acc + 4 * T, a0, a1, a1, a3, d0, T == 0 ? 0 : 1);
    wgmma_rs<N>(acc + 4 * T, b0, b1, b1, b3, d1, 1);
    wgmma_commit();
    wgmma_wait<0>();
    asm volatile("" ::"r"(a0), "r"(a1), "r"(a3), "r"(b0), "r"(b1), "r"(b3));
    ConvStep<T + 1>::run(acc, fp, d0, d1);
  }
};
template <> struct ConvStep<16> {
  static __device__ __forceinline__ void run(float*, const uint32_t*, uint64_t, uint64_t) {}
};

__global__ void __launch_bounds__(K1_THREADS, 1)
conv_mod_kernel(const __nv_bfloat16* __restrict__ kin, const __nv_bfloat16* __restrict__ vin,
                const __nv_bfloat16* __restrict__ shift_k, const __nv_bfloat16* __restrict__ ssm_k,
                const __nv_bfloat16* __restrict__ ssm_D, const __nv_bfloat16* __restrict__ cvec,
                const __nv_bfloat16* __restrict__ w_mod) {
  extern __shared__ __align__(1024) uint8_t smem[];
  const int tid = threadIdx.x;
  const int d0 = blockIdx.x * 4;
  pdl_launch();

  if (tid < 256) {
    const int a = tid >> 1, h = tid & 1;
    const int s0 = 16 * a + 8 * h;
    uint2 kr[11], vr[8];
#pragma unroll
    for (int i = 0; i < 11; i++) {
      int s = s0 - 3 + i;
      kr[i] = (s >= 0) ? __ldg(reinterpret_cast<const uint2*>(kin + (size_t)s * DM + d0)) : make_uint2(0, 0);
    }
#pragma unroll
    for (int i = 0; i < 8; i++) vr[i] = __ldg(reinterpret_cast<const uint2*>(vin + (size_t)(s0 + i) * DM + d0));
    const uint4 wa = __ldg(reinterpret_cast<const uint4*>(shift_k + d0 * 4));
    const uint4 wb = __ldg(reinterpret_cast<const uint4*>(shift_k + d0 * 4 + 8));
    uint32_t W[2][4];
    W[0][0] = prmt(wa.x, wa.z, 0x5410); W[0][1] = prmt(wa.x, wa.z, 0x7632);
    W[0][2] = prmt(wa.y, wa.w, 0x5410); W[0][3] = prmt(wa.y, wa.w, 0x7632);
    W[1][0] = prmt(wb.x, wb.z, 0x5410); W[1][1] = prmt(wb.x, wb.z, 0x7632);
    W[1][2] = prmt(wb.y, wb.w, 0x5410); W[1][3] = prmt(wb.y, wb.w, 0x7632);
#pragma unroll
    for (int p = 0; p < 2; p++) {
      uint32_t kv[8];
#pragma unroll
      for (int i = 0; i < 8; i++) {
        uint32_t ks = bmul2(p ? kr[i].y : kr[i].x, W[p][3]);
        ks = badd2(ks, bmul2(p ? kr[i + 1].y : kr[i + 1].x, W[p][2]));
        ks = badd2(ks, bmul2(p ? kr[i + 2].y : kr[i + 2].x, W[p][1]));
        ks = badd2(ks, bmul2(p ? kr[i + 3].y : kr[i + 3].x, W[p][0]));
        kv[i] = bmul2(ks, p ? vr[i].y : vr[i].x);
      }
      uint4 lo, hi;
      lo.x = prmt(kv[7], kv[6], 0x5410); lo.y = prmt(kv[5], kv[4], 0x5410);
      lo.z = prmt(kv[3], kv[2], 0x5410); lo.w = prmt(kv[1], kv[0], 0x5410);
      hi.x = prmt(kv[7], kv[6], 0x7632); hi.y = prmt(kv[5], kv[4], 0x7632);
      hi.z = prmt(kv[3], kv[2], 0x7632); hi.w = prmt(kv[1], kv[0], 0x7632);
      uint8_t* dst = smem + K1_OFF_U + (2 * p) * U_CH + (1 - h) * U_PLANE + (a + 8) * 16;
      *reinterpret_cast<uint4*>(dst) = lo;
      *reinterpret_cast<uint4*>(dst + U_CH) = hi;
    }
    if (tid < 64) {
      int c = tid >> 4, pl = (tid >> 3) & 1, r = tid & 7;
      *reinterpret_cast<uint4*>(smem + K1_OFF_U + c * U_CH + pl * U_PLANE + r * 16) = make_uint4(0, 0, 0, 0);
    }
  } else {
    const int j = tid - 256;
    const bool do_gemv = blockIdx.x < 96;
    const int vec = j & 3, rg = j >> 2;
    uint4 wv[8];
    unsigned short craw[8];
    if (do_gemv) {
#pragma unroll
      for (int i = 0; i < 8; i++) {
        int row = rg + 64 * i;
        wv[i] = __ldg(reinterpret_cast<const uint4*>(w_mod + (size_t)row * (6 * DM) + blockIdx.x * 32 + vec * 8));
        craw[i] = __ldg(reinterpret_cast<const unsigned short*>(cvec) + row);
      }
    }
    uint4 fv[4];
    uint32_t fx[4];
#pragma unroll
    for (int c = 0; c < 4; c++) {
      const __nv_bfloat16* fr = ssm_k + (size_t)(d0 + c) * S_LEN;
      fv[c] = __ldg(reinterpret_cast<const uint4*>(fr + 8 * j));
      fx[c] = (j < 255) ? (uint32_t)__ldg(reinterpret_cast<const unsigned short*>(fr + 8 * j + 8)) : 0u;
    }
#pragma unroll
    for (int c = 0; c < 4; c++) {
      uint8_t* f0 = smem + K1_OFF_F + c * F_CH;
      uint8_t* f1 = f0 + F_COPY;
      *reinterpret_cast<uint4*>(f0 + 32 + 16 * j) = fv[c];
      uint4 sh;
      sh.x = __funnelshift_r(fv[c].x, fv[c].y, 16);
      sh.y = __funnelshift_r(fv[c].y, fv[c].z, 16);
      sh.z = __funnelshift_r(fv[c].z, fv[c].w, 16);
      sh.w = __funnelshift_r(fv[c].w, fx[c], 16);
      *reinterpret_cast<uint4*>(f1 + 32 + 16 * j) = sh;
      if (j == 0) {
        *reinterpret_cast<uint4*>(f0) = make_uint4(0, 0, 0, 0);
        *reinterpret_cast<uint4*>(f0 + 16) = make_uint4(0, 0, 0, 0);
        *reinterpret_cast<uint4*>(f1) = make_uint4(0, 0, 0, 0);
        *reinterpret_cast<uint4*>(f1 + 16) = make_uint4(0, 0, 0, fv[c].x << 16);
      }
      if (j == 1) {
        *reinterpret_cast<uint4*>(f0 + 32 + 4096) = make_uint4(0, 0, 0, 0);
        *reinterpret_cast<uint4*>(f0 + 32 + 4096 + 16) = make_uint4(0, 0, 0, 0);
        *reinterpret_cast<uint4*>(f1 + 32 + 4096) = make_uint4(0, 0, 0, 0);
        *reinterpret_cast<uint4*>(f1 + 32 + 4096 + 16) = make_uint4(0, 0, 0, 0);
      }
    }
    if (do_gemv) {
      float macc[8];
#pragma unroll
      for (int e = 0; e < 8; e++) macc[e] = 0.f;
#pragma unroll
      for (int i = 0; i < 8; i++) {
        float cf = __uint_as_float((uint32_t)craw[i] << 16);
        float sc = rbf(cf / (1.0f + expf(-cf)));
        macc[0] += sc * bf_lo(wv[i].x); macc[1] += sc * bf_hi(wv[i].x);
        macc[2] += sc * bf_lo(wv[i].y); macc[3] += sc * bf_hi(wv[i].y);
        macc[4] += sc * bf_lo(wv[i].z); macc[5] += sc * bf_hi(wv[i].z);
        macc[6] += sc * bf_lo(wv[i].w); macc[7] += sc * bf_hi(wv[i].w);
      }
#pragma unroll
      for (int e = 0; e < 8; e++) {
        macc[e] += __shfl_xor_sync(0xffffffffu, macc[e], 4);
        macc[e] += __shfl_xor_sync(0xffffffffu, macc[e], 8);
        macc[e] += __shfl_xor_sync(0xffffffffu, macc[e], 16);
      }
      float* red = reinterpret_cast<float*>(smem + K1_OFF_R);
      if ((j & 31) < 4) {
        *reinterpret_cast<float4*>(red + (j >> 5) * 32 + vec * 8) = make_float4(macc[0], macc[1], macc[2], macc[3]);
        *reinterpret_cast<float4*>(red + (j >> 5) * 32 + vec * 8 + 4) = make_float4(macc[4], macc[5], macc[6], macc[7]);
      }
    }
  }
  fence_proxy_async();
  __syncthreads();

  if (blockIdx.x < 96 && tid >= 480) {
    const float* red = reinterpret_cast<const float*>(smem + K1_OFF_R);
    const int l = tid - 480;
    float s = 0.f;
#pragma unroll
    for (int w = 0; w < 8; w++) s += red[w * 32 + l];
    g_mod[blockIdx.x * 32 + l] = __float2bfloat16_rn(s);
  }

  const int warp = tid >> 5, lane = tid & 31;
  const int c = warp >> 2, w = warp & 3;
  const int g8 = lane >> 2, t4 = lane & 3;
  {
    const int x0 = 16 * w + g8 + 2 * t4 - 15;
    const int par = x0 & 1;
    const uint32_t* fp = reinterpret_cast<const uint32_t*>(smem + K1_OFF_F + c * F_CH + par * F_COPY) + ((16 + x0 - par) >> 1);
    float acc[64];
    const uint32_t ubase = smem_u32(smem + K1_OFF_U + c * U_CH);
    const uint64_t dsc0 = make_desc(ubase + 8 * 16, U_PLANE, 128, 0);
    const uint64_t dsc1 = make_desc(ubase + 4 * 16, U_PLANE, 128, 0);
    ConvStep<0>::run(acc, fp, dsc0, dsc1);
    float* P = reinterpret_cast<float*>(smem + K1_OFF_P + c * P_CH) + w * 2048 + t4 * 32;
#pragma unroll
    for (int jj = 0; jj < 16; jj++) {
#pragma unroll
      for (int e = 0; e < 2; e++) {
#pragma unroll
        for (int hi = 0; hi < 2; hi++) {
          int col = (16 * e + g8 + 8 * hi) ^ (8 * t4);
          P[jj * 128 + col] = acc[4 * jj + e + 2 * hi];
        }
      }
    }
  }
  __syncthreads();

  {
    const uint2 dr = __ldg(reinterpret_cast<const uint2*>(ssm_D + d0));
    const int s = 4 * tid;
    uint32_t ylo[4], yhi[4];
#pragma unroll
    for (int cc = 0; cc < 4; cc++) {
      const float* P = reinterpret_cast<const float*>(smem + K1_OFF_P + cc * P_CH);
      float4 sum = make_float4(0.f, 0.f, 0.f, 0.f);
#pragma unroll
      for (int ww = 0; ww < 4; ww++) {
        int sp = s - 16 * ww;
        if (sp >= 0) {
          int aa = sp >> 4, rr = sp & 15;
          int col = (16 * (aa & 1) + rr) ^ (8 * ((aa >> 1) & 3));
          float4 v = *reinterpret_cast<const float4*>(P + ww * 2048 + (aa >> 1) * 32 + col);
          sum.x += v.x; sum.y += v.y; sum.z += v.z; sum.w += v.w;
        }
      }
      const int kidx = 15 - (s & 15);
      const uint8_t* up = smem + K1_OFF_U + cc * U_CH + (kidx >> 3) * U_PLANE + ((s >> 4) + 8) * 16 + ((kidx & 7) - 3) * 2;
      const uint2 kvr = *reinterpret_cast<const uint2*>(up);
      const uint32_t kv01 = prmt(kvr.y, kvr.y, 0x1032);
      const uint32_t kv23 = prmt(kvr.x, kvr.x, 0x1032);
      const uint32_t dcc = (cc & 1) ? prmt(cc < 2 ? dr.x : dr.y, 0, 0x3232) : prmt(cc < 2 ? dr.x : dr.y, 0, 0x1010);
      ylo[cc] = badd2(pack_bf(sum.x, sum.y), bmul2(kv01, dcc));
      yhi[cc] = badd2(pack_bf(sum.z, sum.w), bmul2(kv23, dcc));
    }
    uint2 o;
    __nv_bfloat16* yo = g_yt + (size_t)s * DM + d0;
    o.x = prmt(ylo[0], ylo[1], 0x5410); o.y = prmt(ylo[2], ylo[3], 0x5410);
    *reinterpret_cast<uint2*>(yo) = o;
    o.x = prmt(ylo[0], ylo[1], 0x7632); o.y = prmt(ylo[2], ylo[3], 0x7632);
    *reinterpret_cast<uint2*>(yo + DM) = o;
    o.x = prmt(yhi[0], yhi[1], 0x5410); o.y = prmt(yhi[2], yhi[3], 0x5410);
    *reinterpret_cast<uint2*>(yo + 2 * DM) = o;
    o.x = prmt(yhi[0], yhi[1], 0x7632); o.y = prmt(yhi[2], yhi[3], 0x7632);
    *reinterpret_cast<uint2*>(yo + 3 * DM) = o;
  }
}

__device__ __forceinline__ void row_stats(const uint32_t* x, float& mb, float& rden) {
  float f[16];
#pragma unroll
  for (int i = 0; i < 8; i++) { f[2 * i] = bf_lo(x[i]); f[2 * i + 1] = bf_hi(x[i]); }
  float s0 = 0.f, s1 = 0.f;
#pragma unroll
  for (int i = 0; i < 8; i++) { s0 += f[2 * i]; s1 += f[2 * i + 1]; }
  float sum = s0 + s1;
#pragma unroll
  for (int o = 16; o > 0; o >>= 1) sum += __shfl_xor_sync(0xffffffffu, sum, o);
  const float mean = sum * (1.0f / DM);
  s0 = 0.f; s1 = 0.f;
#pragma unroll
  for (int i = 0; i < 8; i++) {
    float d0 = f[2 * i] - mean, d1 = f[2 * i + 1] - mean;
    s0 += d0 * d0; s1 += d1 * d1;
  }
  float vs = s0 + s1;
#pragma unroll
  for (int o = 16; o > 0; o >>= 1) vs += __shfl_xor_sync(0xffffffffu, vs, o);
  mb = rbf(mean);
  const float den = rbf(sqrtf(rbf(rbf(vs * (1.0f / DM)) + 1e-5f)));
  rden = 1.0f / den;
}
__device__ __forceinline__ uint32_t normalize2(uint32_t x2, uint32_t mb2, float rden) {
  const uint32_t xm = bsub2(x2, mb2);
  return pack_bf(bf_lo(xm) * rden, bf_hi(xm) * rden);
}

__global__ void __launch_bounds__(256) ln_kernel(const __nv_bfloat16* __restrict__ q) {
  const int warp = threadIdx.x >> 5, lane = threadIdx.x & 31;
  const int s = blockIdx.x * 8 + warp;
  pdl_launch();
  uint32_t x[8], yt[8];
  {
    uint4 qa = __ldg(reinterpret_cast<const uint4*>(q + (size_t)s * DM + lane * 8));
    uint4 qb = __ldg(reinterpret_cast<const uint4*>(q + (size_t)s * DM + 256 + lane * 8));
    x[0] = qa.x; x[1] = qa.y; x[2] = qa.z; x[3] = qa.w; x[4] = qb.x; x[5] = qb.y; x[6] = qb.z; x[7] = qb.w;
  }
  float mb, rden;
  row_stats(x, mb, rden);
  pdl_wait();
  uint32_t md[5][8];
  {
    uint4 ya = *reinterpret_cast<const uint4*>(g_yt + (size_t)s * DM + lane * 8);
    uint4 yb = *reinterpret_cast<const uint4*>(g_yt + (size_t)s * DM + 256 + lane * 8);
    yt[0] = ya.x; yt[1] = ya.y; yt[2] = ya.z; yt[3] = ya.w; yt[4] = yb.x; yt[5] = yb.y; yt[6] = yb.z; yt[7] = yb.w;
#pragma unroll
    for (int m = 0; m < 5; m++) {
      uint4 a = *reinterpret_cast<const uint4*>(g_mod + m * DM + lane * 8);
      uint4 b = *reinterpret_cast<const uint4*>(g_mod + m * DM + 256 + lane * 8);
      md[m][0] = a.x; md[m][1] = a.y; md[m][2] = a.z; md[m][3] = a.w;
      md[m][4] = b.x; md[m][5] = b.y; md[m][6] = b.z; md[m][7] = b.w;
    }
  }
  const uint32_t ONE2 = 0x3f803f80u;
  uint32_t mb2 = pack_bf(mb, mb);
  uint32_t x1[8];
#pragma unroll
  for (int i = 0; i < 8; i++) {
    uint32_t ln = normalize2(x[i], mb2, rden);
    uint32_t h = badd2(bmul2(ln, badd2(ONE2, md[1][i])), md[0][i]);
    uint32_t av = bmul2(h, yt[i]);
    x1[i] = badd2(x[i], bmul2(md[2][i], av));
  }
  row_stats(x1, mb, rden);
  mb2 = pack_bf(mb, mb);
  uint32_t h2[8];
#pragma unroll
  for (int i = 0; i < 8; i++) {
    uint32_t ln = normalize2(x1[i], mb2, rden);
    h2[i] = badd2(bmul2(ln, badd2(ONE2, md[4][i])), md[3][i]);
  }
  *reinterpret_cast<uint4*>(g_x1 + (size_t)s * DM + lane * 8) = make_uint4(x1[0], x1[1], x1[2], x1[3]);
  *reinterpret_cast<uint4*>(g_x1 + (size_t)s * DM + 256 + lane * 8) = make_uint4(x1[4], x1[5], x1[6], x1[7]);
  *reinterpret_cast<uint4*>(g_h2 + (size_t)s * DM + lane * 8) = make_uint4(h2[0], h2[1], h2[2], h2[3]);
  *reinterpret_cast<uint4*>(g_h2 + (size_t)s * DM + 256 + lane * 8) = make_uint4(h2[4], h2[5], h2[6], h2[7]);
}

__device__ __forceinline__ void mbar_init(uint32_t bar, uint32_t count) {
  asm volatile("mbarrier.init.shared::cta.b64 [%0], %1;" ::"r"(bar), "r"(count) : "memory");
}
__device__ __forceinline__ void mbar_expect_tx(uint32_t bar, uint32_t bytes) {
  asm volatile("mbarrier.arrive.expect_tx.shared::cta.b64 _, [%0], %1;" ::"r"(bar), "r"(bytes) : "memory");
}
__device__ __forceinline__ void mbar_arrive(uint32_t bar) {
  asm volatile("mbarrier.arrive.shared::cta.b64 _, [%0];" ::"r"(bar) : "memory");
}
__device__ __forceinline__ void mbar_wait(uint32_t bar, uint32_t parity) {
  asm volatile(
      "{\n.reg .pred p;\n"
      "WAIT_LOOP:\n"
      "mbarrier.try_wait.parity.shared::cta.b64 p, [%0], %1, 0x989680;\n"
      "@p bra WAIT_DONE;\n"
      "bra WAIT_LOOP;\n"
      "WAIT_DONE:\n}\n" ::"r"(bar), "r"(parity) : "memory");
}
__device__ __forceinline__ void tma_load_2d(uint32_t dst, const CUtensorMap* tm, uint32_t bar, int c0, int c1) {
  asm volatile(
      "cp.async.bulk.tensor.2d.shared::cluster.global.mbarrier::complete_tx::bytes [%0], [%1, {%3, %4}], [%2];"
      ::"r"(dst), "l"(reinterpret_cast<uint64_t>(tm)), "r"(bar), "r"(c0), "r"(c1) : "memory");
}

template <int BN, int STAGES, int EPI>
__global__ void __launch_bounds__(384, 1)
gemm_kernel(const __grid_constant__ CUtensorMap tmA, const __grid_constant__ CUtensorMap tmB, int K,
            __nv_bfloat16* __restrict__ outp, int ldo) {
  constexpr int A_BYTES = 128 * 64 * 2;
  constexpr int B_BYTES = BN * 64 * 2;
  constexpr int STAGE_BYTES = A_BYTES + B_BYTES;
  extern __shared__ __align__(1024) uint8_t smem[];
  __shared__ __align__(8) uint64_t bars[2 * STAGES];
  const int tid = threadIdx.x, warp = tid >> 5, lane = tid & 31;
  const int m0 = blockIdx.y * 128, n0 = blockIdx.x * BN;
  const uint32_t sbase = smem_u32(smem);
  const uint32_t full0 = smem_u32(&bars[0]), empty0 = smem_u32(&bars[STAGES]);
  pdl_launch();
  if (tid == 0) {
    for (int i = 0; i < STAGES; i++) { mbar_init(full0 + 8 * i, 1); mbar_init(empty0 + 8 * i, 2); }
    asm volatile("fence.mbarrier_init.release.cluster;" ::: "memory");
  }
  __syncthreads();
  const int nkb = K / 64;
  if (warp >= 8) {
    if (warp == 8 && lane == 0) {
      pdl_wait();
      for (int kb = 0; kb < nkb; kb++) {
        const int st = kb % STAGES;
        mbar_wait(empty0 + 8 * st, ((kb / STAGES) & 1) ^ 1);
        mbar_expect_tx(full0 + 8 * st, STAGE_BYTES);
        const uint32_t sa = sbase + st * STAGE_BYTES;
        tma_load_2d(sa, &tmA, full0 + 8 * st, kb * 64, m0);
#pragma unroll
        for (int nb = 0; nb < BN / 64; nb++)
          tma_load_2d(sa + A_BYTES + nb * 8192, &tmB, full0 + 8 * st, n0 + nb * 64, kb * 64);
      }
    }
  } else {
    const int wg = warp >> 2;
    float acc[BN / 2];
    for (int kb = 0; kb < nkb; kb++) {
      const int st = kb % STAGES;
      mbar_wait(full0 + 8 * st, (kb / STAGES) & 1);
      const uint32_t sa = sbase + st * STAGE_BYTES;
      wgmma_fence();
#pragma unroll
      for (int k = 0; k < 4; k++) {
        uint64_t dA = make_desc(sa + wg * 8192 + k * 32, 16, 1024, 1);
        uint64_t dB = make_desc(sa + A_BYTES + k * 2048, 8192, 1024, 1);
        wgmma_ss<BN>(acc, dA, dB, (kb > 0 || k > 0) ? 1 : 0);
      }
      wgmma_commit();
      if (kb > 0) {
        wgmma_wait<1>();
        if ((tid & 127) == 0) mbar_arrive(empty0 + 8 * ((kb - 1) % STAGES));
      }
    }
    wgmma_wait<0>();
    asm volatile("bar.sync 1, 256;" ::: "memory");
    constexpr int ROWB = BN * 2 + 16;
    uint8_t* stg = smem + wg * (64 * ROWB);
    const int w4 = warp & 3, g8 = lane >> 2, t4 = lane & 3;
#pragma unroll
    for (int j = 0; j < BN / 8; j++) {
      uint32_t p01 = pack_bf(acc[4 * j], acc[4 * j + 1]);
      uint32_t p23 = pack_bf(acc[4 * j + 2], acc[4 * j + 3]);
      if (EPI == 0) {
        p01 = pack_bf(fast_silu(bf_lo(p01)), fast_silu(bf_hi(p01)));
        p23 = pack_bf(fast_silu(bf_lo(p23)), fast_silu(bf_hi(p23)));
      } else {
        const uint32_t gb = *reinterpret_cast<const uint32_t*>(g_mod + 5 * DM + n0 + 8 * j + 2 * t4);
        p01 = bmul2(gb, p01);
        p23 = bmul2(gb, p23);
      }
      *reinterpret_cast<uint32_t*>(stg + (16 * w4 + g8) * ROWB + (8 * j + 2 * t4) * 2) = p01;
      *reinterpret_cast<uint32_t*>(stg + (16 * w4 + g8 + 8) * ROWB + (8 * j + 2 * t4) * 2) = p23;
    }
    asm volatile("bar.sync %0, 128;" ::"r"(2 + wg) : "memory");
    constexpr int VEC_PER_ROW = BN / 8;
    const int t = tid & 127;
#pragma unroll 4
    for (int idx = t; idx < 64 * VEC_PER_ROW; idx += 128) {
      const int r = idx / VEC_PER_ROW, cv = idx % VEC_PER_ROW;
      uint4 v = *reinterpret_cast<const uint4*>(stg + r * ROWB + cv * 16);
      const size_t goff = (size_t)(m0 + wg * 64 + r) * ldo + n0 + cv * 8;
      if (EPI == 1) {
        uint4 xr = *reinterpret_cast<const uint4*>(g_x1 + goff);
        v.x = badd2(xr.x, v.x); v.y = badd2(xr.y, v.y); v.z = badd2(xr.z, v.z); v.w = badd2(xr.w, v.w);
      }
      *reinterpret_cast<uint4*>(outp + goff) = v;
    }
  }
}

typedef CUresult (*PFN_encodeTiled)(CUtensorMap*, CUtensorMapDataType, cuuint32_t, void*, const cuuint64_t*,
                                    const cuuint64_t*, const cuuint32_t*, const cuuint32_t*, CUtensorMapInterleave,
                                    CUtensorMapSwizzle, CUtensorMapL2promotion, CUtensorMapFloatOOBfill);

static void make_tmap(PFN_encodeTiled enc, CUtensorMap* tm, void* ptr, uint64_t inner, uint64_t outer,
                      uint32_t box_inner, uint32_t box_outer) {
  cuuint64_t gdim[2] = {inner, outer};
  cuuint64_t gstr[1] = {inner * 2};
  cuuint32_t box[2] = {box_inner, box_outer};
  cuuint32_t estr[2] = {1, 1};
  enc(tm, CU_TENSOR_MAP_DATA_TYPE_BFLOAT16, 2, ptr, gdim, gstr, box, estr, CU_TENSOR_MAP_INTERLEAVE_NONE,
      CU_TENSOR_MAP_SWIZZLE_128B, CU_TENSOR_MAP_L2_PROMOTION_L2_256B, CU_TENSOR_MAP_FLOAT_OOB_FILL_NONE);
}

constexpr int G1_BN = 256, G1_STAGES = 4;
constexpr int G2_BN = 64, G2_STAGES = 6;

template <typename... KArgs, typename... Args>
static void launch_pdl(void (*kern)(KArgs...), dim3 grid, dim3 block, size_t smem, Args... args) {
  cudaLaunchConfig_t cfg = {};
  cfg.gridDim = grid; cfg.blockDim = block; cfg.dynamicSmemBytes = smem; cfg.stream = cudaStreamPerThread;
  cudaLaunchAttribute at[1];
  at[0].id = cudaLaunchAttributeProgrammaticStreamSerialization;
  at[0].val.programmaticStreamSerializationAllowed = 1;
  cfg.attrs = at; cfg.numAttrs = 1;
  cudaLaunchKernelEx(&cfg, kern, KArgs(args)...);
}

extern "C" void kernel_launch(void* const* d_in, const int* in_sizes, int n_in, void* d_out, int out_size) {
  const __nv_bfloat16* A_q = (const __nv_bfloat16*)d_in[0];
  const __nv_bfloat16* A_k = (const __nv_bfloat16*)d_in[1];
  const __nv_bfloat16* A_v = (const __nv_bfloat16*)d_in[2];
  const __nv_bfloat16* A_shift = (const __nv_bfloat16*)d_in[3];
  const __nv_bfloat16* A_ssmk = (const __nv_bfloat16*)d_in[4];
  const __nv_bfloat16* A_ssmD = (const __nv_bfloat16*)d_in[5];
  const __nv_bfloat16* B_w1 = (const __nv_bfloat16*)d_in[7];
  const __nv_bfloat16* B_w2 = (const __nv_bfloat16*)d_in[8];
  const __nv_bfloat16* cvec = (const __nv_bfloat16*)d_in[9];
  const __nv_bfloat16* w_mod = (const __nv_bfloat16*)d_in[10];

  CUtensorMap tmA1, tmB1, tmA2, tmB2;
  PFN_encodeTiled enc = nullptr;
  cudaDriverEntryPointQueryResult qr;
  cudaGetDriverEntryPoint("cuTensorMapEncodeTiled", (void**)&enc, cudaEnableDefault, &qr);
  void *ph2, *pH;
  cudaGetSymbolAddress(&ph2, g_h2);
  cudaGetSymbolAddress(&pH, g_H);
  make_tmap(enc, &tmA1, ph2, DM, S_LEN, 64, 128);
  make_tmap(enc, &tmB1, (void*)B_w1, FF, DM, 64, 64);
  make_tmap(enc, &tmA2, pH, FF, S_LEN, 64, 128);
  make_tmap(enc, &tmB2, (void*)B_w2, DM, FF, 64, 64);
  const int G1_SMEM = G1_STAGES * (16384 + G1_BN * 128), G2_SMEM = G2_STAGES * (16384 + G2_BN * 128);
  cudaFuncSetAttribute(conv_mod_kernel, cudaFuncAttributeMaxDynamicSharedMemorySize, K1_SMEM);
  cudaFuncSetAttribute(gemm_kernel<G1_BN, G1_STAGES, 0>, cudaFuncAttributeMaxDynamicSharedMemorySize, G1_SMEM);
  cudaFuncSetAttribute(gemm_kernel<G2_BN, G2_STAGES, 1>, cudaFuncAttributeMaxDynamicSharedMemorySize, G2_SMEM);

  launch_pdl(conv_mod_kernel, dim3(128), dim3(K1_THREADS), K1_SMEM, A_k, A_v, A_shift, A_ssmk, A_ssmD, cvec, w_mod);
  launch_pdl(ln_kernel, dim3(256), dim3(256), 0, A_q);
  launch_pdl(gemm_kernel<G1_BN, G1_STAGES, 0>, dim3(FF / G1_BN, S_LEN / 128), dim3(384), G1_SMEM, tmA1, tmB1, DM,
             (__nv_bfloat16*)pH, FF);
  launch_pdl(gemm_kernel<G2_BN, G2_STAGES, 1>, dim3(DM / G2_BN, S_LEN / 128), dim3(384), G2_SMEM, tmA2, tmB2, FF,
             (__nv_bfloat16*)d_out, DM);
}
```

```cpp
#include <cuda_runtime.h>
#include <cuda_bf16.h>
#include <cuda.h>
#include <stdint.h>

constexpr int S_LEN = 2048;
constexpr int DM    = 512;
constexpr int FF    = 1792;

__device__ __nv_bfloat16 g_yt[S_LEN * DM];
__device__ __nv_bfloat16 g_mod[6 * DM];
__device__ __nv_bfloat16 g_x1[S_LEN * DM];
__device__ __nv_bfloat16 g_h2[S_LEN * DM];
__device__ __nv_bfloat16 g_H[S_LEN * FF];

#define TS(k, i, cond)
__device__ __forceinline__ float rbf(float x) { return __bfloat162float(__float2bfloat16_rn(x)); }
__device__ __forceinline__ float bf_lo(uint32_t u) { return __uint_as_float(u << 16); }
__device__ __forceinline__ float bf_hi(uint32_t u) { return __uint_as_float(u & 0xffff0000u); }
__device__ __forceinline__ uint32_t pack_bf(float lo, float hi) {
  uint32_t r;
  asm("cvt.rn.bf16x2.f32 %0, %1, %2;" : "=r"(r) : "f"(hi), "f"(lo));
  return r;
}
__device__ __forceinline__ uint32_t smem_u32(const void* p) { return (uint32_t)__cvta_generic_to_shared(p); }

__device__ __forceinline__ void wgmma_fence() { asm volatile("wgmma.fence.sync.aligned;\n" ::: "memory"); }
__device__ __forceinline__ void wgmma_commit() { asm volatile("wgmma.commit_group.sync.aligned;\n" ::: "memory"); }
template <int N> __device__ __forceinline__ void wgmma_wait() {
  asm volatile("wgmma.wait_group.sync.aligned %0;\n" ::"n"(N) : "memory");
}
__device__ __forceinline__ void fence_proxy_async() { asm volatile("fence.proxy.async.shared::cta;\n" ::: "memory"); }

__device__ __forceinline__ uint64_t make_desc(uint32_t saddr, uint32_t lbo_bytes, uint32_t sbo_bytes, uint32_t layout) {
  uint64_t d = 0;
  d |= (uint64_t)((saddr & 0x3FFFF) >> 4);
  d |= (uint64_t)((lbo_bytes >> 4) & 0x3FFF) << 16;
  d |= (uint64_t)((sbo_bytes >> 4) & 0x3FFF) << 32;
  d |= (uint64_t)layout << 62;
  return d;
}

__device__ __forceinline__ uint32_t bmul2(uint32_t a, uint32_t b) {
  uint32_t r; asm("mul.rn.bf16x2 %0, %1, %2;" : "=r"(r) : "r"(a), "r"(b)); return r; }
__device__ __forceinline__ uint32_t badd2(uint32_t a, uint32_t b) {
  uint32_t r; asm("add.rn.bf16x2 %0, %1, %2;" : "=r"(r) : "r"(a), "r"(b)); return r; }
__device__ __forceinline__ uint32_t bsub2(uint32_t a, uint32_t b) {
  uint32_t r; asm("sub.rn.bf16x2 %0, %1, %2;" : "=r"(r) : "r"(a), "r"(b)); return r; }
__device__ __forceinline__ uint32_t prmt(uint32_t a, uint32_t b, uint32_t sel) {
  uint32_t r; asm("prmt.b32 %0, %1, %2, %3;" : "=r"(r) : "r"(a), "r"(b), "r"(sel)); return r; }
__device__ __forceinline__ float fast_silu(float x) {
  float e, r;
  asm("ex2.approx.ftz.f32 %0, %1;" : "=f"(e) : "f"(x * -1.4426950408889634f));
  asm("rcp.approx.ftz.f32 %0, %1;" : "=f"(r) : "f"(1.0f + e));
  return x * r;
}
__device__ __forceinline__ void pdl_wait() { asm volatile("griddepcontrol.wait;" ::: "memory"); }
__device__ __forceinline__ void pdl_launch() { asm volatile("griddepcontrol.launch_dependents;" ::: "memory"); }

template<int N> __device__ __forceinline__ void wgmma_rs(float* d, uint32_t a0, uint32_t a1, uint32_t a2, uint32_t a3, uint64_t descB, int scaleD);
template<> __device__ __forceinline__ void wgmma_rs<8>(float* d, uint32_t a0, uint32_t a1, uint32_t a2, uint32_t a3, uint64_t descB, int scaleD) {
  asm volatile("{\n.reg .pred p;\nsetp.ne.b32 p, %9, 0;\n"
    "wgmma.mma_async.sync.aligned.m64n8k16.f32.bf16.bf16 {%0, %1, %2, %3}, {%4, %5, %6, %7}, %8, p, 1, 1, 0;\n}\n"
    : "+f"(d[0]), "+f"(d[1]), "+f"(d[2]), "+f"(d[3])
    : "r"(a0), "r"(a1), "r"(a2), "r"(a3), "l"(descB), "r"(scaleD));
}
template<> __device__ __forceinline__ void wgmma_rs<16>(float* d, uint32_t a0, uint32_t a1, uint32_t a2, uint32_t a3, uint64_t descB, int scaleD) {
  asm volatile("{\n.reg .pred p;\nsetp.ne.b32 p, %13, 0;\n"
    "wgmma.mma_async.sync.aligned.m64n16k16.f32.bf16.bf16 {%0, %1, %2, %3, %4, %5, %6, %7}, {%8, %9, %10, %11}, %12, p, 1, 1, 0;\n}\n"
    : "+f"(d[0]), "+f"(d[1]), "+f"(d[2]), "+f"(d[3]), "+f"(d[4]), "+f"(d[5]), "+f"(d[6]), "+f"(d[7])
    : "r"(a0), "r"(a1), "r"(a2), "r"(a3), "l"(descB), "r"(scaleD));
}
template<> __device__ __forceinline__ void wgmma_rs<24>(float* d, uint32_t a0, uint32_t a1, uint32_t a2, uint32_t a3, uint64_t descB, int scaleD) {
  asm volatile("{\n.reg .pred p;\nsetp.ne.b32 p, %17, 0;\n"
    "wgmma.mma_async.sync.aligned.m64n24k16.f32.bf16.bf16 {%0, %1, %2, %3, %4, %5, %6, %7, %8, %9, %10, %11}, {%12, %13, %14, %15}, %16, p, 1, 1, 0;\n}\n"
    : "+f"(d[0]), "+f"(d[1]), "+f"(d[2]), "+f"(d[3]), "+f"(d[4]), "+f"(d[5]), "+f"(d[6]), "+f"(d[7]), "+f"(d[8]), "+f"(d[9]), "+f"(d[10]), "+f"(d[11])
    : "r"(a0), "r"(a1), "r"(a2), "r"(a3), "l"(descB), "r"(scaleD));
}
template<> __device__ __forceinline__ void wgmma_rs<32>(float* d, uint32_t a0, uint32_t a1, uint32_t a2, uint32_t a3, uint64_t descB, int scaleD) {
  asm volatile("{\n.reg .pred p;\nsetp.ne.b32 p, %21, 0;\n"
    "wgmma.mma_async.sync.aligned.m64n32k16.f32.bf16.bf16 {%0, %1, %2, %3, %4, %5, %6, %7, %8, %9, %10, %11, %12, %13, %14, %15}, {%16, %17, %18, %19}, %20, p, 1, 1, 0;\n}\n"
    : "+f"(d[0]), "+f"(d[1]), "+f"(d[2]), "+f"(d[3]), "+f"(d[4]), "+f"(d[5]), "+f"(d[6]), "+f"(d[7]), "+f"(d[8]), "+f"(d[9]), "+f"(d[10]), "+f"(d[11]), "+f"(d[12]), "+f"(d[13]), "+f"(d[14]), "+f"(d[15])
    : "r"(a0), "r"(a1), "r"(a2), "r"(a3), "l"(descB), "r"(scaleD));
}
template<> __device__ __forceinline__ void wgmma_rs<40>(float* d, uint32_t a0, uint32_t a1, uint32_t a2, uint32_t a3, uint64_t descB, int scaleD) {
  asm volatile("{\n.reg .pred p;\nsetp.ne.b32 p, %25, 0;\n"
    "wgmma.mma_async.sync.aligned.m64n40k16.f32.bf16.bf16 {%0, %1, %2, %3, %4, %5, %6, %7, %8, %9, %10, %11, %12, %13, %14, %15, %16, %17, %18, %19}, {%20, %21, %22, %23}, %24, p, 1, 1, 0;\n}\n"
    : "+f"(d[0]), "+f"(d[1]), "+f"(d[2]), "+f"(d[3]), "+f"(d[4]), "+f"(d[5]), "+f"(d[6]), "+f"(d[7]), "+f"(d[8]), "+f"(d[9]), "+f"(d[10]), "+f"(d[11]), "+f"(d[12]), "+f"(d[13]), "+f"(d[14]), "+f"(d[15]), "+f"(d[16]), "+f"(d[17]), "+f"(d[18]), "+f"(d[19])
    : "r"(a0), "r"(a1), "r"(a2), "r"(a3), "l"(descB), "r"(scaleD));
}
template<> __device__ __forceinline__ void wgmma_rs<48>(float* d, uint32_t a0, uint32_t a1, uint32_t a2, uint32_t a3, uint64_t descB, int scaleD) {
  asm volatile("{\n.reg .pred p;\nsetp.ne.b32 p, %29, 0;\n"
    "wgmma.mma_async.sync.aligned.m64n48k16.f32.bf16.bf16 {%0, %1, %2, %3, %4, %5, %6, %7, %8, %9, %10, %11, %12, %13, %14, %15, %16, %17, %18, %19, %20, %21, %22, %23}, {%24, %25, %26, %27}, %28, p, 1, 1, 0;\n}\n"
    : "+f"(d[0]), "+f"(d[1]), "+f"(d[2]), "+f"(d[3]), "+f"(d[4]), "+f"(d[5]), "+f"(d[6]), "+f"(d[7]), "+f"(d[8]), "+f"(d[9]), "+f"(d[10]), "+f"(d[11]), "+f"(d[12]), "+f"(d[13]), "+f"(d[14]), "+f"(d[15]), "+f"(d[16]), "+f"(d[17]), "+f"(d[18]), "+f"(d[19]), "+f"(d[20]), "+f"(d[21]), "+f"(d[22]), "+f"(d[23])
    : "r"(a0), "r"(a1), "r"(a2), "r"(a3), "l"(descB), "r"(scaleD));
}
template<> __device__ __forceinline__ void wgmma_rs<56>(float* d, uint32_t a0, uint32_t a1, uint32_t a2, uint32_t a3, uint64_t descB, int scaleD) {
  asm volatile("{\n.reg .pred p;\nsetp.ne.b32 p, %33, 0;\n"
    "wgmma.mma_async.sync.aligned.m64n56k16.f32.bf16.bf16 {%0, %1, %2, %3, %4, %5, %6, %7, %8, %9, %10, %11, %12, %13, %14, %15, %16, %17, %18, %19, %20, %21, %22, %23, %24, %25, %26, %27}, {%28, %29, %30, %31}, %32, p, 1, 1, 0;\n}\n"
    : "+f"(d[0]), "+f"(d[1]), "+f"(d[2]), "+f"(d[3]), "+f"(d[4]), "+f"(d[5]), "+f"(d[6]), "+f"(d[7]), "+f"(d[8]), "+f"(d[9]), "+f"(d[10]), "+f"(d[11]), "+f"(d[12]), "+f"(d[13]), "+f"(d[14]), "+f"(d[15]), "+f"(d[16]), "+f"(d[17]), "+f"(d[18]), "+f"(d[19]), "+f"(d[20]), "+f"(d[21]), "+f"(d[22]), "+f"(d[23]), "+f"(d[24]), "+f"(d[25]), "+f"(d[26]), "+f"(d[27])
    : "r"(a0), "r"(a1), "r"(a2), "r"(a3), "l"(descB), "r"(scaleD));
}
template<> __device__ __forceinline__ void wgmma_rs<64>(float* d, uint32_t a0, uint32_t a1, uint32_t a2, uint32_t a3, uint64_t descB, int scaleD) {
  asm volatile("{\n.reg .pred p;\nsetp.ne.b32 p, %37, 0;\n"
    "wgmma.mma_async.sync.aligned.m64n64k16.f32.bf16.bf16 {%0, %1, %2, %3, %4, %5, %6, %7, %8, %9, %10, %11, %12, %13, %14, %15, %16, %17, %18, %19, %20, %21, %22, %23, %24, %25, %26, %27, %28, %29, %30, %31}, {%32, %33, %34, %35}, %36, p, 1, 1, 0;\n}\n"
    : "+f"(d[0]), "+f"(d[1]), "+f"(d[2]), "+f"(d[3]), "+f"(d[4]), "+f"(d[5]), "+f"(d[6]), "+f"(d[7]), "+f"(d[8]), "+f"(d[9]), "+f"(d[10]), "+f"(d[11]), "+f"(d[12]), "+f"(d[13]), "+f"(d[14]), "+f"(d[15]), "+f"(d[16]), "+f"(d[17]), "+f"(d[18]), "+f"(d[19]), "+f"(d[20]), "+f"(d[21]), "+f"(d[22]), "+f"(d[23]), "+f"(d[24]), "+f"(d[25]), "+f"(d[26]), "+f"(d[27]), "+f"(d[28]), "+f"(d[29]), "+f"(d[30]), "+f"(d[31])
    : "r"(a0), "r"(a1), "r"(a2), "r"(a3), "l"(descB), "r"(scaleD));
}
template<> __device__ __forceinline__ void wgmma_rs<72>(float* d, uint32_t a0, uint32_t a1, uint32_t a2, uint32_t a3, uint64_t descB, int scaleD) {
  asm volatile("{\n.reg .pred p;\nsetp.ne.b32 p, %41, 0;\n"
    "wgmma.mma_async.sync.aligned.m64n72k16.f32.bf16.bf16 {%0, %1, %2, %3, %4, %5, %6, %7, %8, %9, %10, %11, %12, %13, %14, %15, %16, %17, %18, %19, %20, %21, %22, %23, %24, %25, %26, %27, %28, %29, %30, %31, %32, %33, %34, %35}, {%36, %37, %38, %39}, %40, p, 1, 1, 0;\n}\n"
    : "+f"(d[0]), "+f"(d[1]), "+f"(d[2]), "+f"(d[3]), "+f"(d[4]), "+f"(d[5]), "+f"(d[6]), "+f"(d[7]), "+f"(d[8]), "+f"(d[9]), "+f"(d[10]), "+f"(d[11]), "+f"(d[12]), "+f"(d[13]), "+f"(d[14]), "+f"(d[15]), "+f"(d[16]), "+f"(d[17]), "+f"(d[18]), "+f"(d[19]), "+f"(d[20]), "+f"(d[21]), "+f"(d[22]), "+f"(d[23]), "+f"(d[24]), "+f"(d[25]), "+f"(d[26]), "+f"(d[27]), "+f"(d[28]), "+f"(d[29]), "+f"(d[30]), "+f"(d[31]), "+f"(d[32]), "+f"(d[33]), "+f"(d[34]), "+f"(d[35])
    : "r"(a0), "r"(a1), "r"(a2), "r"(a3), "l"(descB), "r"(scaleD));
}
template<> __device__ __forceinline__ void wgmma_rs<80>(float* d, uint32_t a0, uint32_t a1, uint32_t a2, uint32_t a3, uint64_t descB, int scaleD) {
  asm volatile("{\n.reg .pred p;\nsetp.ne.b32 p, %45, 0;\n"
    "wgmma.mma_async.sync.aligned.m64n80k16.f32.bf16.bf16 {%0, %1, %2, %3, %4, %5, %6, %7, %8, %9, %10, %11, %12, %13, %14, %15, %16, %17, %18, %19, %20, %21, %22, %23, %24, %25, %26, %27, %28, %29, %30, %31, %32, %33, %34, %35, %36, %37, %38, %39}, {%40, %41, %42, %43}, %44, p, 1, 1, 0;\n}\n"
    : "+f"(d[0]), "+f"(d[1]), "+f"(d[2]), "+f"(d[3]), "+f"(d[4]), "+f"(d[5]), "+f"(d[6]), "+f"(d[7]), "+f"(d[8]), "+f"(d[9]), "+f"(d[10]), "+f"(d[11]), "+f"(d[12]), "+f"(d[13]), "+f"(d[14]), "+f"(d[15]), "+f"(d[16]), "+f"(d[17]), "+f"(d[18]), "+f"(d[19]), "+f"(d[20]), "+f"(d[21]), "+f"(d[22]), "+f"(d[23]), "+f"(d[24]), "+f"(d[25]), "+f"(d[26]), "+f"(d[27]), "+f"(d[28]), "+f"(d[29]), "+f"(d[30]), "+f"(d[31]), "+f"(d[32]), "+f"(d[33]), "+f"(d[34]), "+f"(d[35]), "+f"(d[36]), "+f"(d[37]), "+f"(d[38]), "+f"(d[39])
    : "r"(a0), "r"(a1), "r"(a2), "r"(a3), "l"(descB), "r"(scaleD));
}
template<> __device__ __forceinline__ void wgmma_rs<88>(float* d, uint32_t a0, uint32_t a1, uint32_t a2, uint32_t a3, uint64_t descB, int scaleD) {
  asm volatile("{\n.reg .pred p;\nsetp.ne.b32 p, %49, 0;\n"
    "wgmma.mma_async.sync.aligned.m64n88k16.f32.bf16.bf16 {%0, %1, %2, %3, %4, %5, %6, %7, %8, %9, %10, %11, %12, %13, %14, %15, %16, %17, %18, %19, %20, %21, %22, %23, %24, %25, %26, %27, %28, %29, %30, %31, %32, %33, %34, %35, %36, %37, %38, %39, %40, %41, %42, %43}, {%44, %45, %46, %47}, %48, p, 1, 1, 0;\n}\n"
    : "+f"(d[0]), "+f"(d[1]), "+f"(d[2]), "+f"(d[3]), "+f"(d[4]), "+f"(d[5]), "+f"(d[6]), "+f"(d[7]), "+f"(d[8]), "+f"(d[9]), "+f"(d[10]), "+f"(d[11]), "+f"(d[12]), "+f"(d[13]), "+f"(d[14]), "+f"(d[15]), "+f"(d[16]), "+f"(d[17]), "+f"(d[18]), "+f"(d[19]), "+f"(d[20]), "+f"(d[21]), "+f"(d[22]), "+f"(d[23]), "+f"(d[24]), "+f"(d[25]), "+f"(d[26]), "+f"(d[27]), "+f"(d[28]), "+f"(d[29]), "+f"(d[30]), "+f"(d[31]), "+f"(d[32]), "+f"(d[33]), "+f"(d[34]), "+f"(d[35]), "+f"(d[36]), "+f"(d[37]), "+f"(d[38]), "+f"(d[39]), "+f"(d[40]), "+f"(d[41]), "+f"(d[42]), "+f"(d[43])
    : "r"(a0), "r"(a1), "r"(a2), "r"(a3), "l"(descB), "r"(scaleD));
}
template<> __device__ __forceinline__ void wgmma_rs<96>(float* d, uint32_t a0, uint32_t a1, uint32_t a2, uint32_t a3, uint64_t descB, int scaleD) {
  asm volatile("{\n.reg .pred p;\nsetp.ne.b32 p, %53, 0;\n"
    "wgmma.mma_async.sync.aligned.m64n96k16.f32.bf16.bf16 {%0, %1, %2, %3, %4, %5, %6, %7, %8, %9, %10, %11, %12, %13, %14, %15, %16, %17, %18, %19, %20, %21, %22, %23, %24, %25, %26, %27, %28, %29, %30, %31, %32, %33, %34, %35, %36, %37, %38, %39, %40, %41, %42, %43, %44, %45, %46, %47}, {%48, %49, %50, %51}, %52, p, 1, 1, 0;\n}\n"
    : "+f"(d[0]), "+f"(d[1]), "+f"(d[2]), "+f"(d[3]), "+f"(d[4]), "+f"(d[5]), "+f"(d[6]), "+f"(d[7]), "+f"(d[8]), "+f"(d[9]), "+f"(d[10]), "+f"(d[11]), "+f"(d[12]), "+f"(d[13]), "+f"(d[14]), "+f"(d[15]), "+f"(d[16]), "+f"(d[17]), "+f"(d[18]), "+f"(d[19]), "+f"(d[20]), "+f"(d[21]), "+f"(d[22]), "+f"(d[23]), "+f"(d[24]), "+f"(d[25]), "+f"(d[26]), "+f"(d[27]), "+f"(d[28]), "+f"(d[29]), "+f"(d[30]), "+f"(d[31]), "+f"(d[32]), "+f"(d[33]), "+f"(d[34]), "+f"(d[35]), "+f"(d[36]), "+f"(d[37]), "+f"(d[38]), "+f"(d[39]), "+f"(d[40]), "+f"(d[41]), "+f"(d[42]), "+f"(d[43]), "+f"(d[44]), "+f"(d[45]), "+f"(d[46]), "+f"(d[47])
    : "r"(a0), "r"(a1), "r"(a2), "r"(a3), "l"(descB), "r"(scaleD));
}
template<> __device__ __forceinline__ void wgmma_rs<104>(float* d, uint32_t a0, uint32_t a1, uint32_t a2, uint32_t a3, uint64_t descB, int scaleD) {
  asm volatile("{\n.reg .pred p;\nsetp.ne.b32 p, %57, 0;\n"
    "wgmma.mma_async.sync.aligned.m64n104k16.f32.bf16.bf16 {%0, %1, %2, %3, %4, %5, %6, %7, %8, %9, %10, %11, %12, %13, %14, %15, %16, %17, %18, %19, %20, %21, %22, %23, %24, %25, %26, %27, %28, %29, %30, %31, %32, %33, %34, %35, %36, %37, %38, %39, %40, %41, %42, %43, %44, %45, %46, %47, %48, %49, %50, %51}, {%52, %53, %54, %55}, %56, p, 1, 1, 0;\n}\n"
    : "+f"(d[0]), "+f"(d[1]), "+f"(d[2]), "+f"(d[3]), "+f"(d[4]), "+f"(d[5]), "+f"(d[6]), "+f"(d[7]), "+f"(d[8]), "+f"(d[9]), "+f"(d[10]), "+f"(d[11]), "+f"(d[12]), "+f"(d[13]), "+f"(d[14]), "+f"(d[15]), "+f"(d[16]), "+f"(d[17]), "+f"(d[18]), "+f"(d[19]), "+f"(d[20]), "+f"(d[21]), "+f"(d[22]), "+f"(d[23]), "+f"(d[24]), "+f"(d[25]), "+f"(d[26]), "+f"(d[27]), "+f"(d[28]), "+f"(d[29]), "+f"(d[30]), "+f"(d[31]), "+f"(d[32]), "+f"(d[33]), "+f"(d[34]), "+f"(d[35]), "+f"(d[36]), "+f"(d[37]), "+f"(d[38]), "+f"(d[39]), "+f"(d[40]), "+f"(d[41]), "+f"(d[42]), "+f"(d[43]), "+f"(d[44]), "+f"(d[45]), "+f"(d[46]), "+f"(d[47]), "+f"(d[48]), "+f"(d[49]), "+f"(d[50]), "+f"(d[51])
    : "r"(a0), "r"(a1), "r"(a2), "r"(a3), "l"(descB), "r"(scaleD));
}
template<> __device__ __forceinline__ void wgmma_rs<112>(float* d, uint32_t a0, uint32_t a1, uint32_t a2, uint32_t a3, uint64_t descB, int scaleD) {
  asm volatile("{\n.reg .pred p;\nsetp.ne.b32 p, %61, 0;\n"
    "wgmma.mma_async.sync.aligned.m64n112k16.f32.bf16.bf16 {%0, %1, %2, %3, %4, %5, %6, %7, %8, %9, %10, %11, %12, %13, %14, %15, %16, %17, %18, %19, %20, %21, %22, %23, %24, %25, %26, %27, %28, %29, %30, %31, %32, %33, %34, %35, %36, %37, %38, %39, %40, %41, %42, %43, %44, %45, %46, %47, %48, %49, %50, %51, %52, %53, %54, %55}, {%56, %57, %58, %59}, %60, p, 1, 1, 0;\n}\n"
    : "+f"(d[0]), "+f"(d[1]), "+f"(d[2]), "+f"(d[3]), "+f"(d[4]), "+f"(d[5]), "+f"(d[6]), "+f"(d[7]), "+f"(d[8]), "+f"(d[9]), "+f"(d[10]), "+f"(d[11]), "+f"(d[12]), "+f"(d[13]), "+f"(d[14]), "+f"(d[15]), "+f"(d[16]), "+f"(d[17]), "+f"(d[18]), "+f"(d[19]), "+f"(d[20]), "+f"(d[21]), "+f"(d[22]), "+f"(d[23]), "+f"(d[24]), "+f"(d[25]), "+f"(d[26]), "+f"(d[27]), "+f"(d[28]), "+f"(d[29]), "+f"(d[30]), "+f"(d[31]), "+f"(d[32]), "+f"(d[33]), "+f"(d[34]), "+f"(d[35]), "+f"(d[36]), "+f"(d[37]), "+f"(d[38]), "+f"(d[39]), "+f"(d[40]), "+f"(d[41]), "+f"(d[42]), "+f"(d[43]), "+f"(d[44]), "+f"(d[45]), "+f"(d[46]), "+f"(d[47]), "+f"(d[48]), "+f"(d[49]), "+f"(d[50]), "+f"(d[51]), "+f"(d[52]), "+f"(d[53]), "+f"(d[54]), "+f"(d[55])
    : "r"(a0), "r"(a1), "r"(a2), "r"(a3), "l"(descB), "r"(scaleD));
}
template<> __device__ __forceinline__ void wgmma_rs<120>(float* d, uint32_t a0, uint32_t a1, uint32_t a2, uint32_t a3, uint64_t descB, int scaleD) {
  asm volatile("{\n.reg .pred p;\nsetp.ne.b32 p, %65, 0;\n"
    "wgmma.mma_async.sync.aligned.m64n120k16.f32.bf16.bf16 {%0, %1, %2, %3, %4, %5, %6, %7, %8, %9, %10, %11, %12, %13, %14, %15, %16, %17, %18, %19, %20, %21, %22, %23, %24, %25, %26, %27, %28, %29, %30, %31, %32, %33, %34, %35, %36, %37, %38, %39, %40, %41, %42, %43, %44, %45, %46, %47, %48, %49, %50, %51, %52, %53, %54, %55, %56, %57, %58, %59}, {%60, %61, %62, %63}, %64, p, 1, 1, 0;\n}\n"
    : "+f"(d[0]), "+f"(d[1]), "+f"(d[2]), "+f"(d[3]), "+f"(d[4]), "+f"(d[5]), "+f"(d[6]), "+f"(d[7]), "+f"(d[8]), "+f"(d[9]), "+f"(d[10]), "+f"(d[11]), "+f"(d[12]), "+f"(d[13]), "+f"(d[14]), "+f"(d[15]), "+f"(d[16]), "+f"(d[17]), "+f"(d[18]), "+f"(d[19]), "+f"(d[20]), "+f"(d[21]), "+f"(d[22]), "+f"(d[23]), "+f"(d[24]), "+f"(d[25]), "+f"(d[26]), "+f"(d[27]), "+f"(d[28]), "+f"(d[29]), "+f"(d[30]), "+f"(d[31]), "+f"(d[32]), "+f"(d[33]), "+f"(d[34]), "+f"(d[35]), "+f"(d[36]), "+f"(d[37]), "+f"(d[38]), "+f"(d[39]), "+f"(d[40]), "+f"(d[41]), "+f"(d[42]), "+f"(d[43]), "+f"(d[44]), "+f"(d[45]), "+f"(d[46]), "+f"(d[47]), "+f"(d[48]), "+f"(d[49]), "+f"(d[50]), "+f"(d[51]), "+f"(d[52]), "+f"(d[53]), "+f"(d[54]), "+f"(d[55]), "+f"(d[56]), "+f"(d[57]), "+f"(d[58]), "+f"(d[59])
    : "r"(a0), "r"(a1), "r"(a2), "r"(a3), "l"(descB), "r"(scaleD));
}
template<> __device__ __forceinline__ void wgmma_rs<128>(float* d, uint32_t a0, uint32_t a1, uint32_t a2, uint32_t a3, uint64_t descB, int scaleD) {
  asm volatile("{\n.reg .pred p;\nsetp.ne.b32 p, %69, 0;\n"
    "wgmma.mma_async.sync.aligned.m64n128k16.f32.bf16.bf16 {%0, %1, %2, %3, %4, %5, %6, %7, %8, %9, %10, %11, %12, %13, %14, %15, %16, %17, %18, %19, %20, %21, %22, %23, %24, %25, %26, %27, %28, %29, %30, %31, %32, %33, %34, %35, %36, %37, %38, %39, %40, %41, %42, %43, %44, %45, %46, %47, %48, %49, %50, %51, %52, %53, %54, %55, %56, %57, %58, %59, %60, %61, %62, %63}, {%64, %65, %66, %67}, %68, p, 1, 1, 0;\n}\n"
    : "+f"(d[0]), "+f"(d[1]), "+f"(d[2]), "+f"(d[3]), "+f"(d[4]), "+f"(d[5]), "+f"(d[6]), "+f"(d[7]), "+f"(d[8]), "+f"(d[9]), "+f"(d[10]), "+f"(d[11]), "+f"(d[12]), "+f"(d[13]), "+f"(d[14]), "+f"(d[15]), "+f"(d[16]), "+f"(d[17]), "+f"(d[18]), "+f"(d[19]), "+f"(d[20]), "+f"(d[21]), "+f"(d[22]), "+f"(d[23]), "+f"(d[24]), "+f"(d[25]), "+f"(d[26]), "+f"(d[27]), "+f"(d[28]), "+f"(d[29]), "+f"(d[30]), "+f"(d[31]), "+f"(d[32]), "+f"(d[33]), "+f"(d[34]), "+f"(d[35]), "+f"(d[36]), "+f"(d[37]), "+f"(d[38]), "+f"(d[39]), "+f"(d[40]), "+f"(d[41]), "+f"(d[42]), "+f"(d[43]), "+f"(d[44]), "+f"(d[45]), "+f"(d[46]), "+f"(d[47]), "+f"(d[48]), "+f"(d[49]), "+f"(d[50]), "+f"(d[51]), "+f"(d[52]), "+f"(d[53]), "+f"(d[54]), "+f"(d[55]), "+f"(d[56]), "+f"(d[57]), "+f"(d[58]), "+f"(d[59]), "+f"(d[60]), "+f"(d[61]), "+f"(d[62]), "+f"(d[63])
    : "r"(a0), "r"(a1), "r"(a2), "r"(a3), "l"(descB), "r"(scaleD));
}
template<int N> __device__ __forceinline__ void wgmma_ss(float* d, uint64_t descA, uint64_t descB, int scaleD);
template<> __device__ __forceinline__ void wgmma_ss<64>(float* d, uint64_t descA, uint64_t descB, int scaleD) {
  asm volatile("{\n.reg .pred p;\nsetp.ne.b32 p, %34, 0;\n"
    "wgmma.mma_async.sync.aligned.m64n64k16.f32.bf16.bf16 {%0, %1, %2, %3, %4, %5, %6, %7, %8, %9, %10, %11, %12, %13, %14, %15, %16, %17, %18, %19, %20, %21, %22, %23, %24, %25, %26, %27, %28, %29, %30, %31}, %32, %33, p, 1, 1, 0, 1;\n}\n"
    : "+f"(d[0]), "+f"(d[1]), "+f"(d[2]), "+f"(d[3]), "+f"(d[4]), "+f"(d[5]), "+f"(d[6]), "+f"(d[7]), "+f"(d[8]), "+f"(d[9]), "+f"(d[10]), "+f"(d[11]), "+f"(d[12]), "+f"(d[13]), "+f"(d[14]), "+f"(d[15]), "+f"(d[16]), "+f"(d[17]), "+f"(d[18]), "+f"(d[19]), "+f"(d[20]), "+f"(d[21]), "+f"(d[22]), "+f"(d[23]), "+f"(d[24]), "+f"(d[25]), "+f"(d[26]), "+f"(d[27]), "+f"(d[28]), "+f"(d[29]), "+f"(d[30]), "+f"(d[31])
    : "l"(descA), "l"(descB), "r"(scaleD));
}
template<> __device__ __forceinline__ void wgmma_ss<128>(float* d, uint64_t descA, uint64_t descB, int scaleD) {
  asm volatile("{\n.reg .pred p;\nsetp.ne.b32 p, %66, 0;\n"
    "wgmma.mma_async.sync.aligned.m64n128k16.f32.bf16.bf16 {%0, %1, %2, %3, %4, %5, %6, %7, %8, %9, %10, %11, %12, %13, %14, %15, %16, %17, %18, %19, %20, %21, %22, %23, %24, %25, %26, %27, %28, %29, %30, %31, %32, %33, %34, %35, %36, %37, %38, %39, %40, %41, %42, %43, %44, %45, %46, %47, %48, %49, %50, %51, %52, %53, %54, %55, %56, %57, %58, %59, %60, %61, %62, %63}, %64, %65, p, 1, 1, 0, 1;\n}\n"
    : "+f"(d[0]), "+f"(d[1]), "+f"(d[2]), "+f"(d[3]), "+f"(d[4]), "+f"(d[5]), "+f"(d[6]), "+f"(d[7]), "+f"(d[8]), "+f"(d[9]), "+f"(d[10]), "+f"(d[11]), "+f"(d[12]), "+f"(d[13]), "+f"(d[14]), "+f"(d[15]), "+f"(d[16]), "+f"(d[17]), "+f"(d[18]), "+f"(d[19]), "+f"(d[20]), "+f"(d[21]), "+f"(d[22]), "+f"(d[23]), "+f"(d[24]), "+f"(d[25]), "+f"(d[26]), "+f"(d[27]), "+f"(d[28]), "+f"(d[29]), "+f"(d[30]), "+f"(d[31]), "+f"(d[32]), "+f"(d[33]), "+f"(d[34]), "+f"(d[35]), "+f"(d[36]), "+f"(d[37]), "+f"(d[38]), "+f"(d[39]), "+f"(d[40]), "+f"(d[41]), "+f"(d[42]), "+f"(d[43]), "+f"(d[44]), "+f"(d[45]), "+f"(d[46]), "+f"(d[47]), "+f"(d[48]), "+f"(d[49]), "+f"(d[50]), "+f"(d[51]), "+f"(d[52]), "+f"(d[53]), "+f"(d[54]), "+f"(d[55]), "+f"(d[56]), "+f"(d[57]), "+f"(d[58]), "+f"(d[59]), "+f"(d[60]), "+f"(d[61]), "+f"(d[62]), "+f"(d[63])
    : "l"(descA), "l"(descB), "r"(scaleD));
}
template<> __device__ __forceinline__ void wgmma_ss<224>(float* d, uint64_t descA, uint64_t descB, int scaleD) {
  asm volatile("{\n.reg .pred p;\nsetp.ne.b32 p, %114, 0;\n"
    "wgmma.mma_async.sync.aligned.m64n224k16.f32.bf16.bf16 {%0, %1, %2, %3, %4, %5, %6, %7, %8, %9, %10, %11, %12, %13, %14, %15, %16, %17, %18, %19, %20, %21, %22, %23, %24, %25, %26, %27, %28, %29, %30, %31, %32, %33, %34, %35, %36, %37, %38, %39, %40, %41, %42, %43, %44, %45, %46, %47, %48, %49, %50, %51, %52, %53, %54, %55, %56, %57, %58, %59, %60, %61, %62, %63, %64, %65, %66, %67, %68, %69, %70, %71, %72, %73, %74, %75, %76, %77, %78, %79, %80, %81, %82, %83, %84, %85, %86, %87, %88, %89, %90, %91, %92, %93, %94, %95, %96, %97, %98, %99, %100, %101, %102, %103, %104, %105, %106, %107, %108, %109, %110, %111}, %112, %113, p, 1, 1, 0, 1;\n}\n"
    : "+f"(d[0]), "+f"(d[1]), "+f"(d[2]), "+f"(d[3]), "+f"(d[4]), "+f"(d[5]), "+f"(d[6]), "+f"(d[7]), "+f"(d[8]), "+f"(d[9]), "+f"(d[10]), "+f"(d[11]), "+f"(d[12]), "+f"(d[13]), "+f"(d[14]), "+f"(d[15]), "+f"(d[16]), "+f"(d[17]), "+f"(d[18]), "+f"(d[19]), "+f"(d[20]), "+f"(d[21]), "+f"(d[22]), "+f"(d[23]), "+f"(d[24]), "+f"(d[25]), "+f"(d[26]), "+f"(d[27]), "+f"(d[28]), "+f"(d[29]), "+f"(d[30]), "+f"(d[31]), "+f"(d[32]), "+f"(d[33]), "+f"(d[34]), "+f"(d[35]), "+f"(d[36]), "+f"(d[37]), "+f"(d[38]), "+f"(d[39]), "+f"(d[40]), "+f"(d[41]), "+f"(d[42]), "+f"(d[43]), "+f"(d[44]), "+f"(d[45]), "+f"(d[46]), "+f"(d[47]), "+f"(d[48]), "+f"(d[49]), "+f"(d[50]), "+f"(d[51]), "+f"(d[52]), "+f"(d[53]), "+f"(d[54]), "+f"(d[55]), "+f"(d[56]), "+f"(d[57]), "+f"(d[58]), "+f"(d[59]), "+f"(d[60]), "+f"(d[61]), "+f"(d[62]), "+f"(d[63]), "+f"(d[64]), "+f"(d[65]), "+f"(d[66]), "+f"(d[67]), "+f"(d[68]), "+f"(d[69]), "+f"(d[70]), "+f"(d[71]), "+f"(d[72]), "+f"(d[73]), "+f"(d[74]), "+f"(d[75]), "+f"(d[76]), "+f"(d[77]), "+f"(d[78]), "+f"(d[79]), "+f"(d[80]), "+f"(d[81]), "+f"(d[82]), "+f"(d[83]), "+f"(d[84]), "+f"(d[85]), "+f"(d[86]), "+f"(d[87]), "+f"(d[88]), "+f"(d[89]), "+f"(d[90]), "+f"(d[91]), "+f"(d[92]), "+f"(d[93]), "+f"(d[94]), "+f"(d[95]), "+f"(d[96]), "+f"(d[97]), "+f"(d[98]), "+f"(d[99]), "+f"(d[100]), "+f"(d[101]), "+f"(d[102]), "+f"(d[103]), "+f"(d[104]), "+f"(d[105]), "+f"(d[106]), "+f"(d[107]), "+f"(d[108]), "+f"(d[109]), "+f"(d[110]), "+f"(d[111])
    : "l"(descA), "l"(descB), "r"(scaleD));
}
template<> __device__ __forceinline__ void wgmma_ss<256>(float* d, uint64_t descA, uint64_t descB, int scaleD) {
  asm volatile("{\n.reg .pred p;\nsetp.ne.b32 p, %130, 0;\n"
    "wgmma.mma_async.sync.aligned.m64n256k16.f32.bf16.bf16 {%0, %1, %2, %3, %4, %5, %6, %7, %8, %9, %10, %11, %12, %13, %14, %15, %16, %17, %18, %19, %20, %21, %22, %23, %24, %25, %26, %27, %28, %29, %30, %31, %32, %33, %34, %35, %36, %37, %38, %39, %40, %41, %42, %43, %44, %45, %46, %47, %48, %49, %50, %51, %52, %53, %54, %55, %56, %57, %58, %59, %60, %61, %62, %63, %64, %65, %66, %67, %68, %69, %70, %71, %72, %73, %74, %75, %76, %77, %78, %79, %80, %81, %82, %83, %84, %85, %86, %87, %88, %89, %90, %91, %92, %93, %94, %95, %96, %97, %98, %99, %100, %101, %102, %103, %104, %105, %106, %107, %108, %109, %110, %111, %112, %113, %114, %115, %116, %117, %118, %119, %120, %121, %122, %123, %124, %125, %126, %127}, %128, %129, p, 1, 1, 0, 1;\n}\n"
    : "+f"(d[0]), "+f"(d[1]), "+f"(d[2]), "+f"(d[3]), "+f"(d[4]), "+f"(d[5]), "+f"(d[6]), "+f"(d[7]), "+f"(d[8]), "+f"(d[9]), "+f"(d[10]), "+f"(d[11]), "+f"(d[12]), "+f"(d[13]), "+f"(d[14]), "+f"(d[15]), "+f"(d[16]), "+f"(d[17]), "+f"(d[18]), "+f"(d[19]), "+f"(d[20]), "+f"(d[21]), "+f"(d[22]), "+f"(d[23]), "+f"(d[24]), "+f"(d[25]), "+f"(d[26]), "+f"(d[27]), "+f"(d[28]), "+f"(d[29]), "+f"(d[30]), "+f"(d[31]), "+f"(d[32]), "+f"(d[33]), "+f"(d[34]), "+f"(d[35]), "+f"(d[36]), "+f"(d[37]), "+f"(d[38]), "+f"(d[39]), "+f"(d[40]), "+f"(d[41]), "+f"(d[42]), "+f"(d[43]), "+f"(d[44]), "+f"(d[45]), "+f"(d[46]), "+f"(d[47]), "+f"(d[48]), "+f"(d[49]), "+f"(d[50]), "+f"(d[51]), "+f"(d[52]), "+f"(d[53]), "+f"(d[54]), "+f"(d[55]), "+f"(d[56]), "+f"(d[57]), "+f"(d[58]), "+f"(d[59]), "+f"(d[60]), "+f"(d[61]), "+f"(d[62]), "+f"(d[63]), "+f"(d[64]), "+f"(d[65]), "+f"(d[66]), "+f"(d[67]), "+f"(d[68]), "+f"(d[69]), "+f"(d[70]), "+f"(d[71]), "+f"(d[72]), "+f"(d[73]), "+f"(d[74]), "+f"(d[75]), "+f"(d[76]), "+f"(d[77]), "+f"(d[78]), "+f"(d[79]), "+f"(d[80]), "+f"(d[81]), "+f"(d[82]), "+f"(d[83]), "+f"(d[84]), "+f"(d[85]), "+f"(d[86]), "+f"(d[87]), "+f"(d[88]), "+f"(d[89]), "+f"(d[90]), "+f"(d[91]), "+f"(d[92]), "+f"(d[93]), "+f"(d[94]), "+f"(d[95]), "+f"(d[96]), "+f"(d[97]), "+f"(d[98]), "+f"(d[99]), "+f"(d[100]), "+f"(d[101]), "+f"(d[102]), "+f"(d[103]), "+f"(d[104]), "+f"(d[105]), "+f"(d[106]), "+f"(d[107]), "+f"(d[108]), "+f"(d[109]), "+f"(d[110]), "+f"(d[111]), "+f"(d[112]), "+f"(d[113]), "+f"(d[114]), "+f"(d[115]), "+f"(d[116]), "+f"(d[117]), "+f"(d[118]), "+f"(d[119]), "+f"(d[120]), "+f"(d[121]), "+f"(d[122]), "+f"(d[123]), "+f"(d[124]), "+f"(d[125]), "+f"(d[126]), "+f"(d[127])
    : "l"(descA), "l"(descB), "r"(scaleD));
}

__device__ __nv_bfloat16 g_U[DM * S_LEN];

__global__ void __launch_bounds__(256)
kv_mod_kernel(const __nv_bfloat16* __restrict__ kin, const __nv_bfloat16* __restrict__ vin,
              const __nv_bfloat16* __restrict__ shift_k, const __nv_bfloat16* __restrict__ cvec,
              const __nv_bfloat16* __restrict__ w_mod) {
  __shared__ __align__(16) uint8_t stage[128 * 128];
  __shared__ float red[8 * 32];
  const int tid = threadIdx.x;
  TS(4, 0, tid == 0);
  pdl_launch();
  const int rb = blockIdx.x >> 2, cb = blockIdx.x & 3;
  const int tg = tid >> 5, cgrp = tid & 31;
  const int s0 = rb * 64 + tg * 8;
  const int dcol = cb * 128 + cgrp * 4;
  uint2 kr[11], vr[8];
#pragma unroll
  for (int i = 0; i < 11; i++) {
    int s = s0 - 3 + i;
    kr[i] = (s >= 0) ? __ldg(reinterpret_cast<const uint2*>(kin + (size_t)s * DM + dcol)) : make_uint2(0, 0);
  }
#pragma unroll
  for (int i = 0; i < 8; i++) vr[i] = __ldg(reinterpret_cast<const uint2*>(vin + (size_t)(s0 + i) * DM + dcol));
  const uint4 wa = __ldg(reinterpret_cast<const uint4*>(shift_k + dcol * 4));
  const uint4 wb = __ldg(reinterpret_cast<const uint4*>(shift_k + dcol * 4 + 8));
  const bool do_gemv = blockIdx.x < 96;
  const int vec = tid & 3, rg = tid >> 2;
  uint4 wv[8];
  unsigned short craw[8];
  if (do_gemv) {
#pragma unroll
    for (int i = 0; i < 8; i++) {
      int row = rg + 64 * i;
      wv[i] = __ldg(reinterpret_cast<const uint4*>(w_mod + (size_t)row * (6 * DM) + blockIdx.x * 32 + vec * 8));
      craw[i] = __ldg(reinterpret_cast<const unsigned short*>(cvec) + row);
    }
  }
  uint32_t W[2][4];
  W[0][0] = prmt(wa.x, wa.z, 0x5410); W[0][1] = prmt(wa.x, wa.z, 0x7632);
  W[0][2] = prmt(wa.y, wa.w, 0x5410); W[0][3] = prmt(wa.y, wa.w, 0x7632);
  W[1][0] = prmt(wb.x, wb.z, 0x5410); W[1][1] = prmt(wb.x, wb.z, 0x7632);
  W[1][2] = prmt(wb.y, wb.w, 0x5410); W[1][3] = prmt(wb.y, wb.w, 0x7632);
#pragma unroll
  for (int p = 0; p < 2; p++) {
    uint32_t kv[8];
#pragma unroll
    for (int i = 0; i < 8; i++) {
      uint32_t ks = bmul2(p ? kr[i].y : kr[i].x, W[p][3]);
      ks = badd2(ks, bmul2(p ? kr[i + 1].y : kr[i + 1].x, W[p][2]));
      ks = badd2(ks, bmul2(p ? kr[i + 2].y : kr[i + 2].x, W[p][1]));
      ks = badd2(ks, bmul2(p ? kr[i + 3].y : kr[i + 3].x, W[p][0]));
      kv[i] = bmul2(ks, p ? vr[i].y : vr[i].x);
    }
    uint4 lo, hi;
    lo.x = prmt(kv[7], kv[6], 0x5410); lo.y = prmt(kv[5], kv[4], 0x5410);
    lo.z = prmt(kv[3], kv[2], 0x5410); lo.w = prmt(kv[1], kv[0], 0x5410);
    hi.x = prmt(kv[7], kv[6], 0x7632); hi.y = prmt(kv[5], kv[4], 0x7632);
    hi.z = prmt(kv[3], kv[2], 0x7632); hi.w = prmt(kv[1], kv[0], 0x7632);
    uint8_t* dst = stage + (cgrp * 4 + 2 * p) * 128 + (1 - (tg & 1)) * 64 + (tg >> 1) * 16;
    *reinterpret_cast<uint4*>(dst) = lo;
    *reinterpret_cast<uint4*>(dst + 128) = hi;
  }
  if (do_gemv) {
    float macc[8];
#pragma unroll
    for (int e = 0; e < 8; e++) macc[e] = 0.f;
#pragma unroll
    for (int i = 0; i < 8; i++) {
      float cf = __uint_as_float((uint32_t)craw[i] << 16);
      float sc = rbf(cf / (1.0f + expf(-cf)));
      macc[0] += sc * bf_lo(wv[i].x); macc[1] += sc * bf_hi(wv[i].x);
      macc[2] += sc * bf_lo(wv[i].y); macc[3] += sc * bf_hi(wv[i].y);
      macc[4] += sc * bf_lo(wv[i].z); macc[5] += sc * bf_hi(wv[i].z);
      macc[6] += sc * bf_lo(wv[i].w); macc[7] += sc * bf_hi(wv[i].w);
    }
#pragma unroll
    for (int e = 0; e < 8; e++) {
      macc[e] += __shfl_xor_sync(0xffffffffu, macc[e], 4);
      macc[e] += __shfl_xor_sync(0xffffffffu, macc[e], 8);
      macc[e] += __shfl_xor_sync(0xffffffffu, macc[e], 16);
    }
    if ((tid & 31) < 4) {
      *reinterpret_cast<float4*>(red + (tid >> 5) * 32 + vec * 8) = make_float4(macc[0], macc[1], macc[2], macc[3]);
      *reinterpret_cast<float4*>(red + (tid >> 5) * 32 + vec * 8 + 4) = make_float4(macc[4], macc[5], macc[6], macc[7]);
    }
  }
  __syncthreads();
#pragma unroll
  for (int i = 0; i < 4; i++) {
    const int v = tid + 256 * i;
    const int ch = v >> 3, pl = (v >> 2) & 1, ck = v & 3;
    const uint4 x = *reinterpret_cast<const uint4*>(stage + v * 16);
    *reinterpret_cast<uint4*>(g_U + (size_t)(cb * 128 + ch) * S_LEN + pl * 1024 + (rb * 4 + ck) * 8) = x;
  }
  if (do_gemv && tid < 32) {
    float s = 0.f;
#pragma unroll
    for (int w = 0; w < 8; w++) s += red[w * 32 + tid];
    g_mod[blockIdx.x * 32 + tid] = __float2bfloat16_rn(s);
  }
  TS(4, 1, tid == 0);
}

constexpr int K1_THREADS = 512;
constexpr int U_ROWS  = 136;
constexpr int U_PLANE = U_ROWS * 16;
constexpr int U_CH    = 2 * U_PLANE;
constexpr int F_LEN   = 2048 + 32;
constexpr int F_COPY  = F_LEN * 2;
constexpr int F_CH    = 2 * F_COPY;
constexpr int P_CH    = 4 * 2048 * 4;
constexpr int K1_OFF_U = 0;
constexpr int K1_OFF_F = K1_OFF_U + 4 * U_CH;
constexpr int K1_OFF_P = K1_OFF_F + 4 * F_CH;
constexpr int K1_SMEM  = K1_OFF_P + 4 * P_CH;

template <int T> struct ConvStep {
  static __device__ __forceinline__ void run(float* acc, const uint32_t* fp, uint64_t d0, uint64_t d1) {
    constexpr int N = 128 - 8 * T;
    uint32_t a0 = fp[64 * T], a1 = fp[64 * T + 4], a3 = fp[64 * T + 8];
    uint32_t b0 = fp[64 * T + 32], b1 = fp[64 * T + 36], b3 = fp[64 * T + 40];
    wgmma_fence();
    wgmma_rs<N>(acc + 4 * T, a0, a1, a1, a3, d0, T == 0 ? 0 : 1);
    wgmma_rs<N>(acc + 4 * T, b0, b1, b1, b3, d1, 1);
    wgmma_commit();
    wgmma_wait<0>();
    asm volatile("" ::"r"(a0), "r"(a1), "r"(a3), "r"(b0), "r"(b1), "r"(b3));
    ConvStep<T + 1>::run(acc, fp, d0, d1);
  }
};
template <> struct ConvStep<16> {
  static __device__ __forceinline__ void run(float*, const uint32_t*, uint64_t, uint64_t) {}
};

__global__ void __launch_bounds__(K1_THREADS, 1)
conv_kernel(const __nv_bfloat16* __restrict__ ssm_k, const __nv_bfloat16* __restrict__ ssm_D) {
  extern __shared__ __align__(1024) uint8_t smem[];
  __shared__ __align__(8) uint64_t ubar;
  const int tid = threadIdx.x;
  const int d0 = blockIdx.x * 4;
  TS(0, 0, tid == 0);
  pdl_launch();
  if (tid == 0) {
    asm volatile("mbarrier.init.shared::cta.b64 [%0], 1;" ::"r"(smem_u32(&ubar)) : "memory");
    asm volatile("fence.mbarrier_init.release.cluster;" ::: "memory");
    asm volatile("fence.proxy.async;" ::: "memory");
  }
  const uint2 dr = __ldg(reinterpret_cast<const uint2*>(ssm_D + d0));
  {
    uint4 fv[2];
    uint32_t fx[2];
    const int j = tid & 255;
#pragma unroll
    for (int i = 0; i < 2; i++) {
      const int c = (tid >> 8) * 2 + i;
      const __nv_bfloat16* fr = ssm_k + (size_t)(d0 + c) * S_LEN;
      fv[i] = __ldg(reinterpret_cast<const uint4*>(fr + 8 * j));
      fx[i] = (j < 255) ? (uint32_t)__ldg(reinterpret_cast<const unsigned short*>(fr + 8 * j + 8)) : 0u;
    }
    if (tid == 32) {
      pdl_wait();
      const uint32_t bar = smem_u32(&ubar);
      asm volatile("mbarrier.arrive.expect_tx.shared::cta.b64 _, [%0], %1;" ::"r"(bar), "r"(4 * 4096) : "memory");
#pragma unroll
      for (int c = 0; c < 4; c++)
#pragma unroll
        for (int pl = 0; pl < 2; pl++)
          asm volatile("cp.async.bulk.shared::cluster.global.mbarrier::complete_tx::bytes [%0], [%1], %2, [%3];"
                       ::"r"(smem_u32(smem + K1_OFF_U + c * U_CH + pl * U_PLANE + 8 * 16)),
                         "l"(g_U + (size_t)(d0 + c) * S_LEN + pl * 1024), "r"(2048), "r"(bar) : "memory");
    }
#pragma unroll
    for (int i = 0; i < 2; i++) {
      const int c = (tid >> 8) * 2 + i;
      uint8_t* f0 = smem + K1_OFF_F + c * F_CH;
      uint8_t* f1 = f0 + F_COPY;
      *reinterpret_cast<uint4*>(f0 + 32 + 16 * j) = fv[i];
      uint4 sh;
      sh.x = __funnelshift_r(fv[i].x, fv[i].y, 16);
      sh.y = __funnelshift_r(fv[i].y, fv[i].z, 16);
      sh.z = __funnelshift_r(fv[i].z, fv[i].w, 16);
      sh.w = __funnelshift_r(fv[i].w, fx[i], 16);
      *reinterpret_cast<uint4*>(f1 + 32 + 16 * j) = sh;
      if (j == 0) {
        *reinterpret_cast<uint4*>(f0) = make_uint4(0, 0, 0, 0);
        *reinterpret_cast<uint4*>(f0 + 16) = make_uint4(0, 0, 0, 0);
        *reinterpret_cast<uint4*>(f1) = make_uint4(0, 0, 0, 0);
        *reinterpret_cast<uint4*>(f1 + 16) = make_uint4(0, 0, 0, fv[i].x << 16);
      }
      if (j == 1) {
        *reinterpret_cast<uint4*>(f0 + 32 + 4096) = make_uint4(0, 0, 0, 0);
        *reinterpret_cast<uint4*>(f0 + 32 + 4096 + 16) = make_uint4(0, 0, 0, 0);
        *reinterpret_cast<uint4*>(f1 + 32 + 4096) = make_uint4(0, 0, 0, 0);
        *reinterpret_cast<uint4*>(f1 + 32 + 4096 + 16) = make_uint4(0, 0, 0, 0);
      }
    }
    if (tid >= 64 && tid < 128) {
      int q = tid - 64, c = q >> 4, pl = (q >> 3) & 1, r = q & 7;
      *reinterpret_cast<uint4*>(smem + K1_OFF_U + c * U_CH + pl * U_PLANE + r * 16) = make_uint4(0, 0, 0, 0);
    }
  }
  TS(0, 1, tid == 0);
  fence_proxy_async();
  __syncthreads();
  {
    const uint32_t bar = smem_u32(&ubar);
    asm volatile(
        "{\n.reg .pred p;\n"
        "K1_WAIT:\n"
        "mbarrier.try_wait.parity.shared::cta.b64 p, [%0], 0, 0x989680;\n"
        "@p bra K1_DONE;\n"
        "bra K1_WAIT;\n"
        "K1_DONE:\n}\n" ::"r"(bar) : "memory");
  }
  TS(0, 2, tid == 0);

  const int warp = tid >> 5, lane = tid & 31;
  const int c = warp >> 2, w = warp & 3;
  const int g8 = lane >> 2, t4 = lane & 3;
  {
    const int x0 = 16 * w + g8 + 2 * t4 - 15;
    const int par = x0 & 1;
    const uint32_t* fp = reinterpret_cast<const uint32_t*>(smem + K1_OFF_F + c * F_CH + par * F_COPY) + ((16 + x0 - par) >> 1);
    float acc[64];
    const uint32_t ubase = smem_u32(smem + K1_OFF_U + c * U_CH);
    const uint64_t dsc0 = make_desc(ubase + 8 * 16, U_PLANE, 128, 0);
    const uint64_t dsc1 = make_desc(ubase + 4 * 16, U_PLANE, 128, 0);
    ConvStep<0>::run(acc, fp, dsc0, dsc1);
    TS(0, 3, tid == 0);
    float* P = reinterpret_cast<float*>(smem + K1_OFF_P + c * P_CH) + w * 2048 + t4 * 32;
#pragma unroll
    for (int jj = 0; jj < 16; jj++) {
#pragma unroll
      for (int e = 0; e < 2; e++) {
#pragma unroll
        for (int hi = 0; hi < 2; hi++) {
          int col = (16 * e + g8 + 8 * hi) ^ (8 * t4);
          P[jj * 128 + col] = acc[4 * jj + e + 2 * hi];
        }
      }
    }
  }
  __syncthreads();
  TS(0, 4, tid == 0);

  {
    const int s = 4 * tid;
    uint32_t ylo[4], yhi[4];
#pragma unroll
    for (int cc = 0; cc < 4; cc++) {
      const float* P = reinterpret_cast<const float*>(smem + K1_OFF_P + cc * P_CH);
      float4 sum = make_float4(0.f, 0.f, 0.f, 0.f);
#pragma unroll
      for (int ww = 0; ww < 4; ww++) {
        int sp = s - 16 * ww;
        if (sp >= 0) {
          int aa = sp >> 4, rr = sp & 15;
          int col = (16 * (aa & 1) + rr) ^ (8 * ((aa >> 1) & 3));
          float4 v = *reinterpret_cast<const float4*>(P + ww * 2048 + (aa >> 1) * 32 + col);
          sum.x += v.x; sum.y += v.y; sum.z += v.z; sum.w += v.w;
        }
      }
      const int kidx = 15 - (s & 15);
      const uint8_t* up = smem + K1_OFF_U + cc * U_CH + (kidx >> 3) * U_PLANE + ((s >> 4) + 8) * 16 + ((kidx & 7) - 3) * 2;
      const uint2 kvr = *reinterpret_cast<const uint2*>(up);
      const uint32_t kv01 = prmt(kvr.y, kvr.y, 0x1032);
      const uint32_t kv23 = prmt(kvr.x, kvr.x, 0x1032);
      const uint32_t dcc = (cc & 1) ? prmt(cc < 2 ? dr.x : dr.y, 0, 0x3232) : prmt(cc < 2 ? dr.x : dr.y, 0, 0x1010);
      ylo[cc] = badd2(pack_bf(sum.x, sum.y), bmul2(kv01, dcc));
      yhi[cc] = badd2(pack_bf(sum.z, sum.w), bmul2(kv23, dcc));
    }
    uint4 o0, o1;
    o0.x = prmt(ylo[0], ylo[1], 0x5410); o0.y = prmt(ylo[2], ylo[3], 0x5410);
    o0.z = prmt(ylo[0], ylo[1], 0x7632); o0.w = prmt(ylo[2], ylo[3], 0x7632);
    o1.x = prmt(yhi[0], yhi[1], 0x5410); o1.y = prmt(yhi[2], yhi[3], 0x5410);
    o1.z = prmt(yhi[0], yhi[1], 0x7632); o1.w = prmt(yhi[2], yhi[3], 0x7632);
    uint4* yo = reinterpret_cast<uint4*>(g_yt + ((size_t)blockIdx.x * S_LEN + s) * 4);
    yo[0] = o0;
    yo[1] = o1;
  }
  TS(0, 5, tid == 0);
}

__device__ __forceinline__ void row_stats(const uint32_t* x, float& mb, float& rden) {
  float f[16];
#pragma unroll
  for (int i = 0; i < 8; i++) { f[2 * i] = bf_lo(x[i]); f[2 * i + 1] = bf_hi(x[i]); }
  float s0 = 0.f, s1 = 0.f;
#pragma unroll
  for (int i = 0; i < 8; i++) { s0 += f[2 * i]; s1 += f[2 * i + 1]; }
  float sum = s0 + s1;
#pragma unroll
  for (int o = 16; o > 0; o >>= 1) sum += __shfl_xor_sync(0xffffffffu, sum, o);
  const float mean = sum * (1.0f / DM);
  s0 = 0.f; s1 = 0.f;
#pragma unroll
  for (int i = 0; i < 8; i++) {
    float d0 = f[2 * i] - mean, d1 = f[2 * i + 1] - mean;
    s0 += d0 * d0; s1 += d1 * d1;
  }
  float vs = s0 + s1;
#pragma unroll
  for (int o = 16; o > 0; o >>= 1) vs += __shfl_xor_sync(0xffffffffu, vs, o);
  mb = rbf(mean);
  const float den = rbf(sqrtf(rbf(rbf(vs * (1.0f / DM)) + 1e-5f)));
  rden = 1.0f / den;
}
__device__ __forceinline__ uint32_t normalize2(uint32_t x2, uint32_t mb2, float rden) {
  const uint32_t xm = bsub2(x2, mb2);
  return pack_bf(bf_lo(xm) * rden, bf_hi(xm) * rden);
}

__global__ void __launch_bounds__(256) ln_kernel(const __nv_bfloat16* __restrict__ q) {
  const int warp = threadIdx.x >> 5, lane = threadIdx.x & 31;
  const int s = blockIdx.x * 8 + warp;
  TS(1, 0, threadIdx.x == 0);
  pdl_launch();
  uint32_t x[8], yt[8];
  {
    uint4 qa = __ldg(reinterpret_cast<const uint4*>(q + (size_t)s * DM + lane * 8));
    uint4 qb = __ldg(reinterpret_cast<const uint4*>(q + (size_t)s * DM + 256 + lane * 8));
    x[0] = qa.x; x[1] = qa.y; x[2] = qa.z; x[3] = qa.w; x[4] = qb.x; x[5] = qb.y; x[6] = qb.z; x[7] = qb.w;
  }
  float mb, rden;
  row_stats(x, mb, rden);
  pdl_wait();
  TS(1, 1, threadIdx.x == 0);
  uint32_t md[5][8];
  {
#pragma unroll
    for (int b = 0; b < 4; b++) {
      const int blk = (b < 2) ? (2 * lane + b) : (64 + 2 * lane + (b - 2));
      const uint2 y = *reinterpret_cast<const uint2*>(g_yt + ((size_t)blk * S_LEN + s) * 4);
      yt[2 * b] = y.x; yt[2 * b + 1] = y.y;
    }
#pragma unroll
    for (int m = 0; m < 5; m++) {
      uint4 a = *reinterpret_cast<const uint4*>(g_mod + m * DM + lane * 8);
      uint4 b = *reinterpret_cast<const uint4*>(g_mod + m * DM + 256 + lane * 8);
      md[m][0] = a.x; md[m][1] = a.y; md[m][2] = a.z; md[m][3] = a.w;
      md[m][4] = b.x; md[m][5] = b.y; md[m][6] = b.z; md[m][7] = b.w;
    }
  }
  const uint32_t ONE2 = 0x3f803f80u;
  uint32_t mb2 = pack_bf(mb, mb);
  uint32_t x1[8];
#pragma unroll
  for (int i = 0; i < 8; i++) {
    uint32_t ln = normalize2(x[i], mb2, rden);
    uint32_t h = badd2(bmul2(ln, badd2(ONE2, md[1][i])), md[0][i]);
    uint32_t av = bmul2(h, yt[i]);
    x1[i] = badd2(x[i], bmul2(md[2][i], av));
  }
  row_stats(x1, mb, rden);
  mb2 = pack_bf(mb, mb);
  uint32_t h2[8];
#pragma unroll
  for (int i = 0; i < 8; i++) {
    uint32_t ln = normalize2(x1[i], mb2, rden);
    h2[i] = badd2(bmul2(ln, badd2(ONE2, md[4][i])), md[3][i]);
  }
  *reinterpret_cast<uint4*>(g_x1 + (size_t)s * DM + lane * 8) = make_uint4(x1[0], x1[1], x1[2], x1[3]);
  *reinterpret_cast<uint4*>(g_x1 + (size_t)s * DM + 256 + lane * 8) = make_uint4(x1[4], x1[5], x1[6], x1[7]);
  *reinterpret_cast<uint4*>(g_h2 + (size_t)s * DM + lane * 8) = make_uint4(h2[0], h2[1], h2[2], h2[3]);
  *reinterpret_cast<uint4*>(g_h2 + (size_t)s * DM + 256 + lane * 8) = make_uint4(h2[4], h2[5], h2[6], h2[7]);
  TS(1, 2, threadIdx.x == 0);
}

__device__ __forceinline__ uint32_t mapa(uint32_t addr, uint32_t rank) {
  uint32_t r; asm("mapa.shared::cluster.u32 %0, %1, %2;" : "=r"(r) : "r"(addr), "r"(rank)); return r; }
__device__ __forceinline__ void st_cluster_v4(uint32_t addr, uint4 v) {
  asm volatile("st.shared::cluster.v4.b32 [%0], {%1, %2, %3, %4};" ::"r"(addr), "r"(v.x), "r"(v.y), "r"(v.z), "r"(v.w) : "memory"); }
__device__ __forceinline__ void mbar_init(uint32_t bar, uint32_t count) {
  asm volatile("mbarrier.init.shared::cta.b64 [%0], %1;" ::"r"(bar), "r"(count) : "memory");
}
__device__ __forceinline__ void mbar_expect_tx(uint32_t bar, uint32_t bytes) {
  asm volatile("mbarrier.arrive.expect_tx.shared::cta.b64 _, [%0], %1;" ::"r"(bar), "r"(bytes) : "memory");
}
__device__ __forceinline__ void mbar_arrive(uint32_t bar) {
  asm volatile("mbarrier.arrive.shared::cta.b64 _, [%0];" ::"r"(bar) : "memory");
}
__device__ __forceinline__ void mbar_wait(uint32_t bar, uint32_t parity) {
  asm volatile(
      "{\n.reg .pred p;\n"
      "WAIT_LOOP:\n"
      "mbarrier.try_wait.parity.shared::cta.b64 p, [%0], %1, 0x989680;\n"
      "@p bra WAIT_DONE;\n"
      "bra WAIT_LOOP;\n"
      "WAIT_DONE:\n}\n" ::"r"(bar), "r"(parity) : "memory");
}
__device__ __forceinline__ void tma_load_2d(uint32_t dst, const CUtensorMap* tm, uint32_t bar, int c0, int c1) {
  asm volatile(
      "cp.async.bulk.tensor.2d.shared::cluster.global.mbarrier::complete_tx::bytes [%0], [%1, {%3, %4}], [%2];"
      ::"r"(dst), "l"(reinterpret_cast<uint64_t>(tm)), "r"(bar), "r"(c0), "r"(c1) : "memory");
}

__device__ __forceinline__ void tma_load_2d_mc(uint32_t dst, const CUtensorMap* tm, uint32_t bar, int c0, int c1, uint16_t mask) {
  asm volatile(
      "cp.async.bulk.tensor.2d.shared::cluster.global.mbarrier::complete_tx::bytes.multicast::cluster [%0], [%1, {%3, %4}], [%2], %5;"
      ::"r"(dst), "l"(reinterpret_cast<uint64_t>(tm)), "r"(bar), "r"(c0), "r"(c1), "h"(mask) : "memory");
}
__device__ __forceinline__ void mbar_arrive_remote(uint32_t bar, uint32_t rank) {
  asm volatile("{\n.reg .b32 ra;\nmapa.shared::cluster.u32 ra, %0, %1;\nmbarrier.arrive.shared::cluster.b64 _, [ra];\n}\n"
               ::"r"(bar), "r"(rank) : "memory");
}
template <int BN, int STAGES, int EPI, int CL>
__global__ void __launch_bounds__(384, 1)
gemm_kernel(const __grid_constant__ CUtensorMap tmA, const __grid_constant__ CUtensorMap tmB, int K,
            __nv_bfloat16* __restrict__ outp, int ldo) {
  constexpr int A_BYTES = 128 * 64 * 2;
  constexpr int B_BYTES = BN * 64 * 2;
  constexpr int STAGE_BYTES = A_BYTES + B_BYTES;
  extern __shared__ __align__(1024) uint8_t smem[];
  __shared__ __align__(8) uint64_t bars[2 * STAGES];
  const int tid = threadIdx.x, warp = tid >> 5, lane = tid & 31;
  const int m0 = blockIdx.y * 128, n0 = blockIdx.x * BN;
  const uint32_t sbase = smem_u32(smem);
  const uint32_t full0 = smem_u32(&bars[0]), empty0 = smem_u32(&bars[STAGES]);
  TS(2 + EPI, 0, tid == 0);
  pdl_launch();
  if (tid == 0) {
    for (int i = 0; i < STAGES; i++) { mbar_init(full0 + 8 * i, 1); mbar_init(empty0 + 8 * i, 2 * CL); }
    asm volatile("fence.mbarrier_init.release.cluster;" ::: "memory");
  }
  if (CL > 1) {
    asm volatile("barrier.cluster.arrive.release.aligned;" ::: "memory");
    asm volatile("barrier.cluster.wait.acquire.aligned;" ::: "memory");
  } else {
    __syncthreads();
  }
  const int nkb = K / 64;
  if (warp >= 8) {
    if (warp == 8 && lane == 0) {
      pdl_wait();
      TS(2 + EPI, 8, true);
      for (int kb = 0; kb < nkb; kb++) {
        const int st = kb % STAGES;
        mbar_wait(empty0 + 8 * st, ((kb / STAGES) & 1) ^ 1);
        mbar_expect_tx(full0 + 8 * st, STAGE_BYTES);
        const uint32_t sa = sbase + st * STAGE_BYTES;
        if (CL == 1) {
          tma_load_2d(sa, &tmA, full0 + 8 * st, kb * 64, m0);
        } else {
          const uint32_t rank = blockIdx.x & (CL - 1);
          tma_load_2d_mc(sa + rank * (A_BYTES / CL), &tmA, full0 + 8 * st, kb * 64, m0 + rank * (128 / CL), (uint16_t)((1 << CL) - 1));
        }
#pragma unroll
        for (int nb = 0; nb < BN / 64; nb++)
          tma_load_2d(sa + A_BYTES + nb * 8192, &tmB, full0 + 8 * st, n0 + nb * 64, kb * 64);
      }
    }
  } else {
    const int wg = warp >> 2;
    float acc[BN / 2];
    for (int kb = 0; kb < nkb; kb++) {
      const int st = kb % STAGES;
      mbar_wait(full0 + 8 * st, (kb / STAGES) & 1);
      if (kb == 0) TS(2 + EPI, 2, tid == 0);
      const uint32_t sa = sbase + st * STAGE_BYTES;
      wgmma_fence();
#pragma unroll
      for (int k = 0; k < 4; k++) {
        uint64_t dA = make_desc(sa + wg * 8192 + k * 32, 16, 1024, 1);
        uint64_t dB = make_desc(sa + A_BYTES + k * 2048, 8192, 1024, 1);
        wgmma_ss<BN>(acc, dA, dB, (kb > 0 || k > 0) ? 1 : 0);
      }
      wgmma_commit();
      if (kb > 0) {
        wgmma_wait<1>();
        if ((tid & 127) == 0) {
          if (CL == 1) mbar_arrive(empty0 + 8 * ((kb - 1) % STAGES));
          else {
#pragma unroll
            for (int r = 0; r < CL; r++) mbar_arrive_remote(empty0 + 8 * ((kb - 1) % STAGES), r);
          }
        }
      }
    }
    wgmma_wait<0>();
    TS(2 + EPI, 3, tid == 0);
    asm volatile("bar.sync 1, 256;" ::: "memory");
    constexpr int ROWB = BN * 2 + 16;
    uint8_t* stg = smem + wg * (64 * ROWB);
    const int w4 = warp & 3, g8 = lane >> 2, t4 = lane & 3;
#pragma unroll
    for (int j = 0; j < BN / 8; j++) {
      uint32_t p01 = pack_bf(acc[4 * j], acc[4 * j + 1]);
      uint32_t p23 = pack_bf(acc[4 * j + 2], acc[4 * j + 3]);
      if (EPI == 0) {
        p01 = pack_bf(fast_silu(bf_lo(p01)), fast_silu(bf_hi(p01)));
        p23 = pack_bf(fast_silu(bf_lo(p23)), fast_silu(bf_hi(p23)));
      } else {
        const uint32_t gb = *reinterpret_cast<const uint32_t*>(g_mod + 5 * DM + n0 + 8 * j + 2 * t4);
        p01 = bmul2(gb, p01);
        p23 = bmul2(gb, p23);
      }
      *reinterpret_cast<uint32_t*>(stg + (16 * w4 + g8) * ROWB + (8 * j + 2 * t4) * 2) = p01;
      *reinterpret_cast<uint32_t*>(stg + (16 * w4 + g8 + 8) * ROWB + (8 * j + 2 * t4) * 2) = p23;
    }
    asm volatile("bar.sync %0, 128;" ::"r"(2 + wg) : "memory");
    TS(2 + EPI, 4, tid == 0);
    constexpr int VEC_PER_ROW = BN / 8;
    const int t = tid & 127;
#pragma unroll 4
    for (int idx = t; idx < 64 * VEC_PER_ROW; idx += 128) {
      const int r = idx / VEC_PER_ROW, cv = idx % VEC_PER_ROW;
      uint4 v = *reinterpret_cast<const uint4*>(stg + r * ROWB + cv * 16);
      const size_t goff = (size_t)(m0 + wg * 64 + r) * ldo + n0 + cv * 8;
      if (EPI == 1) {
        uint4 xr = *reinterpret_cast<const uint4*>(g_x1 + goff);
        v.x = badd2(xr.x, v.x); v.y = badd2(xr.y, v.y); v.z = badd2(xr.z, v.z); v.w = badd2(xr.w, v.w);
      }
      *reinterpret_cast<uint4*>(outp + goff) = v;
    }
    TS(2 + EPI, 5, tid == 0);
  }
  if (CL > 1) {
    asm volatile("barrier.cluster.arrive.release.aligned;" ::: "memory");
    asm volatile("barrier.cluster.wait.acquire.aligned;" ::: "memory");
  }
}

constexpr int G2_STAGES = 5;
constexpr int G2_STAGE_BYTES = 16384 + 16384;
constexpr int G2_XCHG = G2_STAGES * G2_STAGE_BYTES;
constexpr int G2_SMEM = G2_XCHG + 32768;

__global__ void __launch_bounds__(384, 1)
gemm2_kernel(const __grid_constant__ CUtensorMap tmA, const __grid_constant__ CUtensorMap tmB,
             __nv_bfloat16* __restrict__ outp) {
  extern __shared__ __align__(1024) uint8_t smem[];
  __shared__ __align__(8) uint64_t bars[2 * G2_STAGES];
  const int tid = threadIdx.x, warp = tid >> 5, lane = tid & 31;
  const uint32_t rank = blockIdx.x & 1;
  const int m0 = blockIdx.y * 128, n0 = (blockIdx.x >> 1) * 128;
  const int kb0 = rank * 14;
  const uint32_t sbase = smem_u32(smem);
  const uint32_t full0 = smem_u32(&bars[0]), empty0 = smem_u32(&bars[G2_STAGES]);
  TS(3, 0, tid == 0);
  pdl_launch();
  if (tid == 0) {
    for (int i = 0; i < G2_STAGES; i++) { mbar_init(full0 + 8 * i, 1); mbar_init(empty0 + 8 * i, 2); }
    asm volatile("fence.mbarrier_init.release.cluster;" ::: "memory");
  }
  __syncthreads();
  const int wg = warp >> 2;
  const int t = tid & 127;
  float acc[64];
  if (warp >= 8) {
    if (warp == 8 && lane == 0) {
      pdl_wait();
      TS(3, 8, true);
      for (int kb = 0; kb < 14; kb++) {
        const int st = kb % G2_STAGES;
        mbar_wait(empty0 + 8 * st, ((kb / G2_STAGES) & 1) ^ 1);
        mbar_expect_tx(full0 + 8 * st, G2_STAGE_BYTES);
        const uint32_t sa = sbase + st * G2_STAGE_BYTES;
        tma_load_2d(sa, &tmA, full0 + 8 * st, (kb0 + kb) * 64, m0);
        tma_load_2d(sa + 16384, &tmB, full0 + 8 * st, n0, (kb0 + kb) * 64);
        tma_load_2d(sa + 16384 + 8192, &tmB, full0 + 8 * st, n0 + 64, (kb0 + kb) * 64);
      }
    }
  } else {
    for (int kb = 0; kb < 14; kb++) {
      const int st = kb % G2_STAGES;
      mbar_wait(full0 + 8 * st, (kb / G2_STAGES) & 1);
      if (kb == 0) TS(3, 2, tid == 0);
      const uint32_t sa = sbase + st * G2_STAGE_BYTES;
      wgmma_fence();
#pragma unroll
      for (int k = 0; k < 4; k++) {
        uint64_t dA = make_desc(sa + wg * 8192 + k * 32, 16, 1024, 1);
        uint64_t dB = make_desc(sa + 16384 + k * 2048, 8192, 1024, 1);
        wgmma_ss<128>(acc, dA, dB, (kb > 0 || k > 0) ? 1 : 0);
      }
      wgmma_commit();
      if (kb > 0) {
        wgmma_wait<1>();
        if (t == 0) mbar_arrive(empty0 + 8 * ((kb - 1) % G2_STAGES));
      }
    }
    wgmma_wait<0>();
    TS(3, 3, tid == 0);
    if (wg != (int)rank) {
      const uint32_t dst = mapa(sbase + G2_XCHG + t * 16, rank ^ 1);
#pragma unroll
      for (int i = 0; i < 16; i++)
        st_cluster_v4(dst + i * 2048, make_uint4(__float_as_uint(acc[4 * i]), __float_as_uint(acc[4 * i + 1]),
                                                 __float_as_uint(acc[4 * i + 2]), __float_as_uint(acc[4 * i + 3])));
    }
  }
  asm volatile("barrier.cluster.arrive.release.aligned;" ::: "memory");
  asm volatile("barrier.cluster.wait.acquire.aligned;" ::: "memory");
  if (warp < 8 && wg == (int)rank) {
    const int w4 = warp & 3, g8 = lane >> 2, t4 = lane & 3;
    constexpr int ROWB = 128 * 2 + 16;
    uint8_t* stg = smem;
#pragma unroll
    for (int j = 0; j < 16; j++) {
      const uint4 pr = *reinterpret_cast<const uint4*>(smem + G2_XCHG + j * 2048 + t * 16);
      const uint32_t gb = *reinterpret_cast<const uint32_t*>(g_mod + 5 * DM + n0 + 8 * j + 2 * t4);
      uint32_t p01 = pack_bf(acc[4 * j] + __uint_as_float(pr.x), acc[4 * j + 1] + __uint_as_float(pr.y));
      uint32_t p23 = pack_bf(acc[4 * j + 2] + __uint_as_float(pr.z), acc[4 * j + 3] + __uint_as_float(pr.w));
      p01 = bmul2(gb, p01);
      p23 = bmul2(gb, p23);
      *reinterpret_cast<uint32_t*>(stg + (16 * w4 + g8) * ROWB + (8 * j + 2 * t4) * 2) = p01;
      *reinterpret_cast<uint32_t*>(stg + (16 * w4 + g8 + 8) * ROWB + (8 * j + 2 * t4) * 2) = p23;
    }
    asm volatile("bar.sync 2, 128;" ::: "memory");
    TS(3, 4, t == 0);
#pragma unroll
    for (int i = 0; i < 8; i++) {
      const int idx = t + 128 * i;
      const int r = idx >> 4, cv = idx & 15;
      uint4 v = *reinterpret_cast<const uint4*>(stg + r * ROWB + cv * 16);
      const size_t goff = (size_t)(m0 + rank * 64 + r) * DM + n0 + cv * 8;
      const uint4 xr = *reinterpret_cast<const uint4*>(g_x1 + goff);
      v.x = badd2(xr.x, v.x); v.y = badd2(xr.y, v.y); v.z = badd2(xr.z, v.z); v.w = badd2(xr.w, v.w);
      *reinterpret_cast<uint4*>(outp + goff) = v;
    }
    TS(3, 5, t == 0);
  }
}

typedef CUresult (*PFN_encodeTiled)(CUtensorMap*, CUtensorMapDataType, cuuint32_t, void*, const cuuint64_t*,
                                    const cuuint64_t*, const cuuint32_t*, const cuuint32_t*, CUtensorMapInterleave,
                                    CUtensorMapSwizzle, CUtensorMapL2promotion, CUtensorMapFloatOOBfill);

static void make_tmap(PFN_encodeTiled enc, CUtensorMap* tm, void* ptr, uint64_t inner, uint64_t outer,
                      uint32_t box_inner, uint32_t box_outer) {
  cuuint64_t gdim[2] = {inner, outer};
  cuuint64_t gstr[1] = {inner * 2};
  cuuint32_t box[2] = {box_inner, box_outer};
  cuuint32_t estr[2] = {1, 1};
  enc(tm, CU_TENSOR_MAP_DATA_TYPE_BFLOAT16, 2, ptr, gdim, gstr, box, estr, CU_TENSOR_MAP_INTERLEAVE_NONE,
      CU_TENSOR_MAP_SWIZZLE_128B, CU_TENSOR_MAP_L2_PROMOTION_L2_256B, CU_TENSOR_MAP_FLOAT_OOB_FILL_NONE);
}

constexpr int G1_BN = 256, G1_STAGES = 4, G1_CL = 1;

template <typename... KArgs, typename... Args>
static void launch_pdl(void (*kern)(KArgs...), dim3 grid, dim3 block, size_t smem, int cluster_x, Args... args) {
  cudaLaunchConfig_t cfg = {};
  cfg.gridDim = grid; cfg.blockDim = block; cfg.dynamicSmemBytes = smem; cfg.stream = cudaStreamPerThread;
  cudaLaunchAttribute at[2];
  at[0].id = cudaLaunchAttributeProgrammaticStreamSerialization;
  at[0].val.programmaticStreamSerializationAllowed = 1;
  at[1].id = cudaLaunchAttributeClusterDimension;
  at[1].val.clusterDim.x = cluster_x; at[1].val.clusterDim.y = 1; at[1].val.clusterDim.z = 1;
  cfg.attrs = at; cfg.numAttrs = cluster_x > 1 ? 2 : 1;
  cudaLaunchKernelEx(&cfg, kern, KArgs(args)...);
}

extern "C" void kernel_launch(void* const* d_in, const int* in_sizes, int n_in, void* d_out, int out_size) {
  const __nv_bfloat16* A_q = (const __nv_bfloat16*)d_in[0];
  const __nv_bfloat16* A_k = (const __nv_bfloat16*)d_in[1];
  const __nv_bfloat16* A_v = (const __nv_bfloat16*)d_in[2];
  const __nv_bfloat16* A_shift = (const __nv_bfloat16*)d_in[3];
  const __nv_bfloat16* A_ssmk = (const __nv_bfloat16*)d_in[4];
  const __nv_bfloat16* A_ssmD = (const __nv_bfloat16*)d_in[5];
  const __nv_bfloat16* B_w1 = (const __nv_bfloat16*)d_in[7];
  const __nv_bfloat16* B_w2 = (const __nv_bfloat16*)d_in[8];
  const __nv_bfloat16* cvec = (const __nv_bfloat16*)d_in[9];
  const __nv_bfloat16* w_mod = (const __nv_bfloat16*)d_in[10];

  CUtensorMap tmA1, tmB1, tmA2, tmB2;
  PFN_encodeTiled enc = nullptr;
  cudaDriverEntryPointQueryResult qr;
  cudaGetDriverEntryPoint("cuTensorMapEncodeTiled", (void**)&enc, cudaEnableDefault, &qr);
  void *ph2, *pH;
  cudaGetSymbolAddress(&ph2, g_h2);
  cudaGetSymbolAddress(&pH, g_H);
  make_tmap(enc, &tmA1, ph2, DM, S_LEN, 64, 128 / G1_CL);
  make_tmap(enc, &tmB1, (void*)B_w1, FF, DM, 64, 64);
  make_tmap(enc, &tmA2, pH, FF, S_LEN, 64, 128);
  make_tmap(enc, &tmB2, (void*)B_w2, DM, FF, 64, 64);
  const int G1_SMEM = G1_STAGES * (16384 + G1_BN * 128);
  cudaFuncSetAttribute(conv_kernel, cudaFuncAttributeMaxDynamicSharedMemorySize, K1_SMEM);
  cudaFuncSetAttribute(gemm_kernel<G1_BN, G1_STAGES, 0, G1_CL>, cudaFuncAttributeMaxDynamicSharedMemorySize, G1_SMEM);
  cudaFuncSetAttribute(gemm2_kernel, cudaFuncAttributeMaxDynamicSharedMemorySize, G2_SMEM);

  launch_pdl(kv_mod_kernel, dim3(128), dim3(256), 0, 1, A_k, A_v, A_shift, cvec, w_mod);
  launch_pdl(conv_kernel, dim3(128), dim3(K1_THREADS), K1_SMEM, 1, A_ssmk, A_ssmD);
  launch_pdl(ln_kernel, dim3(256), dim3(256), 0, 1, A_q);
  launch_pdl(gemm_kernel<G1_BN, G1_STAGES, 0, G1_CL>, dim3(FF / G1_BN, S_LEN / 128), dim3(384), G1_SMEM, G1_CL, tmA1, tmB1, DM,
             (__nv_bfloat16*)pH, FF);
  launch_pdl(gemm2_kernel, dim3(8, S_LEN / 128), dim3(384), G2_SMEM, 2, tmA2, tmB2, (__nv_bfloat16*)d_out);
}
```

```cpp
#include <cuda_runtime.h>
#include <cuda_bf16.h>
#include <cuda.h>
#include <stdint.h>

constexpr int S_LEN = 2048;
constexpr int DM    = 512;
constexpr int FF    = 1792;

__device__ __nv_bfloat16 g_yt[S_LEN * DM];
__device__ __nv_bfloat16 g_mod[6 * DM];
__device__ __nv_bfloat16 g_x1[S_LEN * DM];
__device__ __nv_bfloat16 g_h2[S_LEN * DM];
__device__ __nv_bfloat16 g_H[S_LEN * FF];

#define TS(k, i, cond)
__device__ __forceinline__ float rbf(float x) { return __bfloat162float(__float2bfloat16_rn(x)); }
__device__ __forceinline__ float bf_lo(uint32_t u) { return __uint_as_float(u << 16); }
__device__ __forceinline__ float bf_hi(uint32_t u) { return __uint_as_float(u & 0xffff0000u); }
__device__ __forceinline__ uint32_t pack_bf(float lo, float hi) {
  uint32_t r;
  asm("cvt.rn.bf16x2.f32 %0, %1, %2;" : "=r"(r) : "f"(hi), "f"(lo));
  return r;
}
__device__ __forceinline__ uint32_t smem_u32(const void* p) { return (uint32_t)__cvta_generic_to_shared(p); }

__device__ __forceinline__ void wgmma_fence() { asm volatile("wgmma.fence.sync.aligned;\n" ::: "memory"); }
__device__ __forceinline__ void wgmma_commit() { asm volatile("wgmma.commit_group.sync.aligned;\n" ::: "memory"); }
template <int N> __device__ __forceinline__ void wgmma_wait() {
  asm volatile("wgmma.wait_group.sync.aligned %0;\n" ::"n"(N) : "memory");
}
__device__ __forceinline__ void fence_proxy_async() { asm volatile("fence.proxy.async.shared::cta;\n" ::: "memory"); }

__device__ __forceinline__ uint64_t make_desc(uint32_t saddr, uint32_t lbo_bytes, uint32_t sbo_bytes, uint32_t layout) {
  uint64_t d = 0;
  d |= (uint64_t)((saddr & 0x3FFFF) >> 4);
  d |= (uint64_t)((lbo_bytes >> 4) & 0x3FFF) << 16;
  d |= (uint64_t)((sbo_bytes >> 4) & 0x3FFF) << 32;
  d |= (uint64_t)layout << 62;
  return d;
}

__device__ __forceinline__ uint32_t bmul2(uint32_t a, uint32_t b) {
  uint32_t r; asm("mul.rn.bf16x2 %0, %1, %2;" : "=r"(r) : "r"(a), "r"(b)); return r; }
__device__ __forceinline__ uint32_t badd2(uint32_t a, uint32_t b) {
  uint32_t r; asm("add.rn.bf16x2 %0, %1, %2;" : "=r"(r) : "r"(a), "r"(b)); return r; }
__device__ __forceinline__ uint32_t bsub2(uint32_t a, uint32_t b) {
  uint32_t r; asm("sub.rn.bf16x2 %0, %1, %2;" : "=r"(r) : "r"(a), "r"(b)); return r; }
__device__ __forceinline__ uint32_t prmt(uint32_t a, uint32_t b, uint32_t sel) {
  uint32_t r; asm("prmt.b32 %0, %1, %2, %3;" : "=r"(r) : "r"(a), "r"(b), "r"(sel)); return r; }
__device__ __forceinline__ float fast_silu(float x) {
  float e, r;
  asm("ex2.approx.ftz.f32 %0, %1;" : "=f"(e) : "f"(x * -1.4426950408889634f));
  asm("rcp.approx.ftz.f32 %0, %1;" : "=f"(r) : "f"(1.0f + e));
  return x * r;
}
__device__ __forceinline__ void pdl_wait() { asm volatile("griddepcontrol.wait;" ::: "memory"); }
__device__ __forceinline__ void pdl_launch() { asm volatile("griddepcontrol.launch_dependents;" ::: "memory"); }

template<int N> __device__ __forceinline__ void wgmma_rs(float* d, uint32_t a0, uint32_t a1, uint32_t a2, uint32_t a3, uint64_t descB, int scaleD);
template<> __device__ __forceinline__ void wgmma_rs<8>(float* d, uint32_t a0, uint32_t a1, uint32_t a2, uint32_t a3, uint64_t descB, int scaleD) {
  asm volatile("{\n.reg .pred p;\nsetp.ne.b32 p, %9, 0;\n"
    "wgmma.mma_async.sync.aligned.m64n8k16.f32.bf16.bf16 {%0, %1, %2, %3}, {%4, %5, %6, %7}, %8, p, 1, 1, 0;\n}\n"
    : "+f"(d[0]), "+f"(d[1]), "+f"(d[2]), "+f"(d[3])
    : "r"(a0), "r"(a1), "r"(a2), "r"(a3), "l"(descB), "r"(scaleD));
}
template<> __device__ __forceinline__ void wgmma_rs<16>(float* d, uint32_t a0, uint32_t a1, uint32_t a2, uint32_t a3, uint64_t descB, int scaleD) {
  asm volatile("{\n.reg .pred p;\nsetp.ne.b32 p, %13, 0;\n"
    "wgmma.mma_async.sync.aligned.m64n16k16.f32.bf16.bf16 {%0, %1, %2, %3, %4, %5, %6, %7}, {%8, %9, %10, %11}, %12, p, 1, 1, 0;\n}\n"
    : "+f"(d[0]), "+f"(d[1]), "+f"(d[2]), "+f"(d[3]), "+f"(d[4]), "+f"(d[5]), "+f"(d[6]), "+f"(d[7])
    : "r"(a0), "r"(a1), "r"(a2), "r"(a3), "l"(descB), "r"(scaleD));
}
template<> __device__ __forceinline__ void wgmma_rs<24>(float* d, uint32_t a0, uint32_t a1, uint32_t a2, uint32_t a3, uint64_t descB, int scaleD) {
  asm volatile("{\n.reg .pred p;\nsetp.ne.b32 p, %17, 0;\n"
    "wgmma.mma_async.sync.aligned.m64n24k16.f32.bf16.bf16 {%0, %1, %2, %3, %4, %5, %6, %7, %8, %9, %10, %11}, {%12, %13, %14, %15}, %16, p, 1, 1, 0;\n}\n"
    : "+f"(d[0]), "+f"(d[1]), "+f"(d[2]), "+f"(d[3]), "+f"(d[4]), "+f"(d[5]), "+f"(d[6]), "+f"(d[7]), "+f"(d[8]), "+f"(d[9]), "+f"(d[10]), "+f"(d[11])
    : "r"(a0), "r"(a1), "r"(a2), "r"(a3), "l"(descB), "r"(scaleD));
}
template<> __device__ __forceinline__ void wgmma_rs<32>(float* d, uint32_t a0, uint32_t a1, uint32_t a2, uint32_t a3, uint64_t descB, int scaleD) {
  asm volatile("{\n.reg .pred p;\nsetp.ne.b32 p, %21, 0;\n"
    "wgmma.mma_async.sync.aligned.m64n32k16.f32.bf16.bf16 {%0, %1, %2, %3, %4, %5, %6, %7, %8, %9, %10, %11, %12, %13, %14, %15}, {%16, %17, %18, %19}, %20, p, 1, 1, 0;\n}\n"
    : "+f"(d[0]), "+f"(d[1]), "+f"(d[2]), "+f"(d[3]), "+f"(d[4]), "+f"(d[5]), "+f"(d[6]), "+f"(d[7]), "+f"(d[8]), "+f"(d[9]), "+f"(d[10]), "+f"(d[11]), "+f"(d[12]), "+f"(d[13]), "+f"(d[14]), "+f"(d[15])
    : "r"(a0), "r"(a1), "r"(a2), "r"(a3), "l"(descB), "r"(scaleD));
}
template<> __device__ __forceinline__ void wgmma_rs<40>(float* d, uint32_t a0, uint32_t a1, uint32_t a2, uint32_t a3, uint64_t descB, int scaleD) {
  asm volatile("{\n.reg .pred p;\nsetp.ne.b32 p, %25, 0;\n"
    "wgmma.mma_async.sync.aligned.m64n40k16.f32.bf16.bf16 {%0, %1, %2, %3, %4, %5, %6, %7, %8, %9, %10, %11, %12, %13, %14, %15, %16, %17, %18, %19}, {%20, %21, %22, %23}, %24, p, 1, 1, 0;\n}\n"
    : "+f"(d[0]), "+f"(d[1]), "+f"(d[2]), "+f"(d[3]), "+f"(d[4]), "+f"(d[5]), "+f"(d[6]), "+f"(d[7]), "+f"(d[8]), "+f"(d[9]), "+f"(d[10]), "+f"(d[11]), "+f"(d[12]), "+f"(d[13]), "+f"(d[14]), "+f"(d[15]), "+f"(d[16]), "+f"(d[17]), "+f"(d[18]), "+f"(d[19])
    : "r"(a0), "r"(a1), "r"(a2), "r"(a3), "l"(descB), "r"(scaleD));
}
template<> __device__ __forceinline__ void wgmma_rs<48>(float* d, uint32_t a0, uint32_t a1, uint32_t a2, uint32_t a3, uint64_t descB, int scaleD) {
  asm volatile("{\n.reg .pred p;\nsetp.ne.b32 p, %29, 0;\n"
    "wgmma.mma_async.sync.aligned.m64n48k16.f32.bf16.bf16 {%0, %1, %2, %3, %4, %5, %6, %7, %8, %9, %10, %11, %12, %13, %14, %15, %16, %17, %18, %19, %20, %21, %22, %23}, {%24, %25, %26, %27}, %28, p, 1, 1, 0;\n}\n"
    : "+f"(d[0]), "+f"(d[1]), "+f"(d[2]), "+f"(d[3]), "+f"(d[4]), "+f"(d[5]), "+f"(d[6]), "+f"(d[7]), "+f"(d[8]), "+f"(d[9]), "+f"(d[10]), "+f"(d[11]), "+f"(d[12]), "+f"(d[13]), "+f"(d[14]), "+f"(d[15]), "+f"(d[16]), "+f"(d[17]), "+f"(d[18]), "+f"(d[19]), "+f"(d[20]), "+f"(d[21]), "+f"(d[22]), "+f"(d[23])
    : "r"(a0), "r"(a1), "r"(a2), "r"(a3), "l"(descB), "r"(scaleD));
}
template<> __device__ __forceinline__ void wgmma_rs<56>(float* d, uint32_t a0, uint32_t a1, uint32_t a2, uint32_t a3, uint64_t descB, int scaleD) {
  asm volatile("{\n.reg .pred p;\nsetp.ne.b32 p, %33, 0;\n"
    "wgmma.mma_async.sync.aligned.m64n56k16.f32.bf16.bf16 {%0, %1, %2, %3, %4, %5, %6, %7, %8, %9, %10, %11, %12, %13, %14, %15, %16, %17, %18, %19, %20, %21, %22, %23, %24, %25, %26, %27}, {%28, %29, %30, %31}, %32, p, 1, 1, 0;\n}\n"
    : "+f"(d[0]), "+f"(d[1]), "+f"(d[2]), "+f"(d[3]), "+f"(d[4]), "+f"(d[5]), "+f"(d[6]), "+f"(d[7]), "+f"(d[8]), "+f"(d[9]), "+f"(d[10]), "+f"(d[11]), "+f"(d[12]), "+f"(d[13]), "+f"(d[14]), "+f"(d[15]), "+f"(d[16]), "+f"(d[17]), "+f"(d[18]), "+f"(d[19]), "+f"(d[20]), "+f"(d[21]), "+f"(d[22]), "+f"(d[23]), "+f"(d[24]), "+f"(d[25]), "+f"(d[26]), "+f"(d[27])
    : "r"(a0), "r"(a1), "r"(a2), "r"(a3), "l"(descB), "r"(scaleD));
}
template<> __device__ __forceinline__ void wgmma_rs<64>(float* d, uint32_t a0, uint32_t a1, uint32_t a2, uint32_t a3, uint64_t descB, int scaleD) {
  asm volatile("{\n.reg .pred p;\nsetp.ne.b32 p, %37, 0;\n"
    "wgmma.mma_async.sync.aligned.m64n64k16.f32.bf16.bf16 {%0, %1, %2, %3, %4, %5, %6, %7, %8, %9, %10, %11, %12, %13, %14, %15, %16, %17, %18, %19, %20, %21, %22, %23, %24, %25, %26, %27, %28, %29, %30, %31}, {%32, %33, %34, %35}, %36, p, 1, 1, 0;\n}\n"
    : "+f"(d[0]), "+f"(d[1]), "+f"(d[2]), "+f"(d[3]), "+f"(d[4]), "+f"(d[5]), "+f"(d[6]), "+f"(d[7]), "+f"(d[8]), "+f"(d[9]), "+f"(d[10]), "+f"(d[11]), "+f"(d[12]), "+f"(d[13]), "+f"(d[14]), "+f"(d[15]), "+f"(d[16]), "+f"(d[17]), "+f"(d[18]), "+f"(d[19]), "+f"(d[20]), "+f"(d[21]), "+f"(d[22]), "+f"(d[23]), "+f"(d[24]), "+f"(d[25]), "+f"(d[26]), "+f"(d[27]), "+f"(d[28]), "+f"(d[29]), "+f"(d[30]), "+f"(d[31])
    : "r"(a0), "r"(a1), "r"(a2), "r"(a3), "l"(descB), "r"(scaleD));
}
template<> __device__ __forceinline__ void wgmma_rs<72>(float* d, uint32_t a0, uint32_t a1, uint32_t a2, uint32_t a3, uint64_t descB, int scaleD) {
  asm volatile("{\n.reg .pred p;\nsetp.ne.b32 p, %41, 0;\n"
    "wgmma.mma_async.sync.aligned.m64n72k16.f32.bf16.bf16 {%0, %1, %2, %3, %4, %5, %6, %7, %8, %9, %10, %11, %12, %13, %14, %15, %16, %17, %18, %19, %20, %21, %22, %23, %24, %25, %26, %27, %28, %29, %30, %31, %32, %33, %34, %35}, {%36, %37, %38, %39}, %40, p, 1, 1, 0;\n}\n"
    : "+f"(d[0]), "+f"(d[1]), "+f"(d[2]), "+f"(d[3]), "+f"(d[4]), "+f"(d[5]), "+f"(d[6]), "+f"(d[7]), "+f"(d[8]), "+f"(d[9]), "+f"(d[10]), "+f"(d[11]), "+f"(d[12]), "+f"(d[13]), "+f"(d[14]), "+f"(d[15]), "+f"(d[16]), "+f"(d[17]), "+f"(d[18]), "+f"(d[19]), "+f"(d[20]), "+f"(d[21]), "+f"(d[22]), "+f"(d[23]), "+f"(d[24]), "+f"(d[25]), "+f"(d[26]), "+f"(d[27]), "+f"(d[28]), "+f"(d[29]), "+f"(d[30]), "+f"(d[31]), "+f"(d[32]), "+f"(d[33]), "+f"(d[34]), "+f"(d[35])
    : "r"(a0), "r"(a1), "r"(a2), "r"(a3), "l"(descB), "r"(scaleD));
}
template<> __device__ __forceinline__ void wgmma_rs<80>(float* d, uint32_t a0, uint32_t a1, uint32_t a2, uint32_t a3, uint64_t descB, int scaleD) {
  asm volatile("{\n.reg .pred p;\nsetp.ne.b32 p, %45, 0;\n"
    "wgmma.mma_async.sync.aligned.m64n80k16.f32.bf16.bf16 {%0, %1, %2, %3, %4, %5, %6, %7, %8, %9, %10, %11, %12, %13, %14, %15, %16, %17, %18, %19, %20, %21, %22, %23, %24, %25, %26, %27, %28, %29, %30, %31, %32, %33, %34, %35, %36, %37, %38, %39}, {%40, %41, %42, %43}, %44, p, 1, 1, 0;\n}\n"
    : "+f"(d[0]), "+f"(d[1]), "+f"(d[2]), "+f"(d[3]), "+f"(d[4]), "+f"(d[5]), "+f"(d[6]), "+f"(d[7]), "+f"(d[8]), "+f"(d[9]), "+f"(d[10]), "+f"(d[11]), "+f"(d[12]), "+f"(d[13]), "+f"(d[14]), "+f"(d[15]), "+f"(d[16]), "+f"(d[17]), "+f"(d[18]), "+f"(d[19]), "+f"(d[20]), "+f"(d[21]), "+f"(d[22]), "+f"(d[23]), "+f"(d[24]), "+f"(d[25]), "+f"(d[26]), "+f"(d[27]), "+f"(d[28]), "+f"(d[29]), "+f"(d[30]), "+f"(d[31]), "+f"(d[32]), "+f"(d[33]), "+f"(d[34]), "+f"(d[35]), "+f"(d[36]), "+f"(d[37]), "+f"(d[38]), "+f"(d[39])
    : "r"(a0), "r"(a1), "r"(a2), "r"(a3), "l"(descB), "r"(scaleD));
}
template<> __device__ __forceinline__ void wgmma_rs<88>(float* d, uint32_t a0, uint32_t a1, uint32_t a2, uint32_t a3, uint64_t descB, int scaleD) {
  asm volatile("{\n.reg .pred p;\nsetp.ne.b32 p, %49, 0;\n"
    "wgmma.mma_async.sync.aligned.m64n88k16.f32.bf16.bf16 {%0, %1, %2, %3, %4, %5, %6, %7, %8, %9, %10, %11, %12, %13, %14, %15, %16, %17, %18, %19, %20, %21, %22, %23, %24, %25, %26, %27, %28, %29, %30, %31, %32, %33, %34, %35, %36, %37, %38, %39, %40, %41, %42, %43}, {%44, %45, %46, %47}, %48, p, 1, 1, 0;\n}\n"
    : "+f"(d[0]), "+f"(d[1]), "+f"(d[2]), "+f"(d[3]), "+f"(d[4]), "+f"(d[5]), "+f"(d[6]), "+f"(d[7]), "+f"(d[8]), "+f"(d[9]), "+f"(d[10]), "+f"(d[11]), "+f"(d[12]), "+f"(d[13]), "+f"(d[14]), "+f"(d[15]), "+f"(d[16]), "+f"(d[17]), "+f"(d[18]), "+f"(d[19]), "+f"(d[20]), "+f"(d[21]), "+f"(d[22]), "+f"(d[23]), "+f"(d[24]), "+f"(d[25]), "+f"(d[26]), "+f"(d[27]), "+f"(d[28]), "+f"(d[29]), "+f"(d[30]), "+f"(d[31]), "+f"(d[32]), "+f"(d[33]), "+f"(d[34]), "+f"(d[35]), "+f"(d[36]), "+f"(d[37]), "+f"(d[38]), "+f"(d[39]), "+f"(d[40]), "+f"(d[41]), "+f"(d[42]), "+f"(d[43])
    : "r"(a0), "r"(a1), "r"(a2), "r"(a3), "l"(descB), "r"(scaleD));
}
template<> __device__ __forceinline__ void wgmma_rs<96>(float* d, uint32_t a0, uint32_t a1, uint32_t a2, uint32_t a3, uint64_t descB, int scaleD) {
  asm volatile("{\n.reg .pred p;\nsetp.ne.b32 p, %53, 0;\n"
    "wgmma.mma_async.sync.aligned.m64n96k16.f32.bf16.bf16 {%0, %1, %2, %3, %4, %5, %6, %7, %8, %9, %10, %11, %12, %13, %14, %15, %16, %17, %18, %19, %20, %21, %22, %23, %24, %25, %26, %27, %28, %29, %30, %31, %32, %33, %34, %35, %36, %37, %38, %39, %40, %41, %42, %43, %44, %45, %46, %47}, {%48, %49, %50, %51}, %52, p, 1, 1, 0;\n}\n"
    : "+f"(d[0]), "+f"(d[1]), "+f"(d[2]), "+f"(d[3]), "+f"(d[4]), "+f"(d[5]), "+f"(d[6]), "+f"(d[7]), "+f"(d[8]), "+f"(d[9]), "+f"(d[10]), "+f"(d[11]), "+f"(d[12]), "+f"(d[13]), "+f"(d[14]), "+f"(d[15]), "+f"(d[16]), "+f"(d[17]), "+f"(d[18]), "+f"(d[19]), "+f"(d[20]), "+f"(d[21]), "+f"(d[22]), "+f"(d[23]), "+f"(d[24]), "+f"(d[25]), "+f"(d[26]), "+f"(d[27]), "+f"(d[28]), "+f"(d[29]), "+f"(d[30]), "+f"(d[31]), "+f"(d[32]), "+f"(d[33]), "+f"(d[34]), "+f"(d[35]), "+f"(d[36]), "+f"(d[37]), "+f"(d[38]), "+f"(d[39]), "+f"(d[40]), "+f"(d[41]), "+f"(d[42]), "+f"(d[43]), "+f"(d[44]), "+f"(d[45]), "+f"(d[46]), "+f"(d[47])
    : "r"(a0), "r"(a1), "r"(a2), "r"(a3), "l"(descB), "r"(scaleD));
}
template<> __device__ __forceinline__ void wgmma_rs<104>(float* d, uint32_t a0, uint32_t a1, uint32_t a2, uint32_t a3, uint64_t descB, int scaleD) {
  asm volatile("{\n.reg .pred p;\nsetp.ne.b32 p, %57, 0;\n"
    "wgmma.mma_async.sync.aligned.m64n104k16.f32.bf16.bf16 {%0, %1, %2, %3, %4, %5, %6, %7, %8, %9, %10, %11, %12, %13, %14, %15, %16, %17, %18, %19, %20, %21, %22, %23, %24, %25, %26, %27, %28, %29, %30, %31, %32, %33, %34, %35, %36, %37, %38, %39, %40, %41, %42, %43, %44, %45, %46, %47, %48, %49, %50, %51}, {%52, %53, %54, %55}, %56, p, 1, 1, 0;\n}\n"
    : "+f"(d[0]), "+f"(d[1]), "+f"(d[2]), "+f"(d[3]), "+f"(d[4]), "+f"(d[5]), "+f"(d[6]), "+f"(d[7]), "+f"(d[8]), "+f"(d[9]), "+f"(d[10]), "+f"(d[11]), "+f"(d[12]), "+f"(d[13]), "+f"(d[14]), "+f"(d[15]), "+f"(d[16]), "+f"(d[17]), "+f"(d[18]), "+f"(d[19]), "+f"(d[20]), "+f"(d[21]), "+f"(d[22]), "+f"(d[23]), "+f"(d[24]), "+f"(d[25]), "+f"(d[26]), "+f"(d[27]), "+f"(d[28]), "+f"(d[29]), "+f"(d[30]), "+f"(d[31]), "+f"(d[32]), "+f"(d[33]), "+f"(d[34]), "+f"(d[35]), "+f"(d[36]), "+f"(d[37]), "+f"(d[38]), "+f"(d[39]), "+f"(d[40]), "+f"(d[41]), "+f"(d[42]), "+f"(d[43]), "+f"(d[44]), "+f"(d[45]), "+f"(d[46]), "+f"(d[47]), "+f"(d[48]), "+f"(d[49]), "+f"(d[50]), "+f"(d[51])
    : "r"(a0), "r"(a1), "r"(a2), "r"(a3), "l"(descB), "r"(scaleD));
}
template<> __device__ __forceinline__ void wgmma_rs<112>(float* d, uint32_t a0, uint32_t a1, uint32_t a2, uint32_t a3, uint64_t descB, int scaleD) {
  asm volatile("{\n.reg .pred p;\nsetp.ne.b32 p, %61, 0;\n"
    "wgmma.mma_async.sync.aligned.m64n112k16.f32.bf16.bf16 {%0, %1, %2, %3, %4, %5, %6, %7, %8, %9, %10, %11, %12, %13, %14, %15, %16, %17, %18, %19, %20, %21, %22, %23, %24, %25, %26, %27, %28, %29, %30, %31, %32, %33, %34, %35, %36, %37, %38, %39, %40, %41, %42, %43, %44, %45, %46, %47, %48, %49, %50, %51, %52, %53, %54, %55}, {%56, %57, %58, %59}, %60, p, 1, 1, 0;\n}\n"
    : "+f"(d[0]), "+f"(d[1]), "+f"(d[2]), "+f"(d[3]), "+f"(d[4]), "+f"(d[5]), "+f"(d[6]), "+f"(d[7]), "+f"(d[8]), "+f"(d[9]), "+f"(d[10]), "+f"(d[11]), "+f"(d[12]), "+f"(d[13]), "+f"(d[14]), "+f"(d[15]), "+f"(d[16]), "+f"(d[17]), "+f"(d[18]), "+f"(d[19]), "+f"(d[20]), "+f"(d[21]), "+f"(d[22]), "+f"(d[23]), "+f"(d[24]), "+f"(d[25]), "+f"(d[26]), "+f"(d[27]), "+f"(d[28]), "+f"(d[29]), "+f"(d[30]), "+f"(d[31]), "+f"(d[32]), "+f"(d[33]), "+f"(d[34]), "+f"(d[35]), "+f"(d[36]), "+f"(d[37]), "+f"(d[38]), "+f"(d[39]), "+f"(d[40]), "+f"(d[41]), "+f"(d[42]), "+f"(d[43]), "+f"(d[44]), "+f"(d[45]), "+f"(d[46]), "+f"(d[47]), "+f"(d[48]), "+f"(d[49]), "+f"(d[50]), "+f"(d[51]), "+f"(d[52]), "+f"(d[53]), "+f"(d[54]), "+f"(d[55])
    : "r"(a0), "r"(a1), "r"(a2), "r"(a3), "l"(descB), "r"(scaleD));
}
template<> __device__ __forceinline__ void wgmma_rs<120>(float* d, uint32_t a0, uint32_t a1, uint32_t a2, uint32_t a3, uint64_t descB, int scaleD) {
  asm volatile("{\n.reg .pred p;\nsetp.ne.b32 p, %65, 0;\n"
    "wgmma.mma_async.sync.aligned.m64n120k16.f32.bf16.bf16 {%0, %1, %2, %3, %4, %5, %6, %7, %8, %9, %10, %11, %12, %13, %14, %15, %16, %17, %18, %19, %20, %21, %22, %23, %24, %25, %26, %27, %28, %29, %30, %31, %32, %33, %34, %35, %36, %37, %38, %39, %40, %41, %42, %43, %44, %45, %46, %47, %48, %49, %50, %51, %52, %53, %54, %55, %56, %57, %58, %59}, {%60, %61, %62, %63}, %64, p, 1, 1, 0;\n}\n"
    : "+f"(d[0]), "+f"(d[1]), "+f"(d[2]), "+f"(d[3]), "+f"(d[4]), "+f"(d[5]), "+f"(d[6]), "+f"(d[7]), "+f"(d[8]), "+f"(d[9]), "+f"(d[10]), "+f"(d[11]), "+f"(d[12]), "+f"(d[13]), "+f"(d[14]), "+f"(d[15]), "+f"(d[16]), "+f"(d[17]), "+f"(d[18]), "+f"(d[19]), "+f"(d[20]), "+f"(d[21]), "+f"(d[22]), "+f"(d[23]), "+f"(d[24]), "+f"(d[25]), "+f"(d[26]), "+f"(d[27]), "+f"(d[28]), "+f"(d[29]), "+f"(d[30]), "+f"(d[31]), "+f"(d[32]), "+f"(d[33]), "+f"(d[34]), "+f"(d[35]), "+f"(d[36]), "+f"(d[37]), "+f"(d[38]), "+f"(d[39]), "+f"(d[40]), "+f"(d[41]), "+f"(d[42]), "+f"(d[43]), "+f"(d[44]), "+f"(d[45]), "+f"(d[46]), "+f"(d[47]), "+f"(d[48]), "+f"(d[49]), "+f"(d[50]), "+f"(d[51]), "+f"(d[52]), "+f"(d[53]), "+f"(d[54]), "+f"(d[55]), "+f"(d[56]), "+f"(d[57]), "+f"(d[58]), "+f"(d[59])
    : "r"(a0), "r"(a1), "r"(a2), "r"(a3), "l"(descB), "r"(scaleD));
}
template<> __device__ __forceinline__ void wgmma_rs<128>(float* d, uint32_t a0, uint32_t a1, uint32_t a2, uint32_t a3, uint64_t descB, int scaleD) {
  asm volatile("{\n.reg .pred p;\nsetp.ne.b32 p, %69, 0;\n"
    "wgmma.mma_async.sync.aligned.m64n128k16.f32.bf16.bf16 {%0, %1, %2, %3, %4, %5, %6, %7, %8, %9, %10, %11, %12, %13, %14, %15, %16, %17, %18, %19, %20, %21, %22, %23, %24, %25, %26, %27, %28, %29, %30, %31, %32, %33, %34, %35, %36, %37, %38, %39, %40, %41, %42, %43, %44, %45, %46, %47, %48, %49, %50, %51, %52, %53, %54, %55, %56, %57, %58, %59, %60, %61, %62, %63}, {%64, %65, %66, %67}, %68, p, 1, 1, 0;\n}\n"
    : "+f"(d[0]), "+f"(d[1]), "+f"(d[2]), "+f"(d[3]), "+f"(d[4]), "+f"(d[5]), "+f"(d[6]), "+f"(d[7]), "+f"(d[8]), "+f"(d[9]), "+f"(d[10]), "+f"(d[11]), "+f"(d[12]), "+f"(d[13]), "+f"(d[14]), "+f"(d[15]), "+f"(d[16]), "+f"(d[17]), "+f"(d[18]), "+f"(d[19]), "+f"(d[20]), "+f"(d[21]), "+f"(d[22]), "+f"(d[23]), "+f"(d[24]), "+f"(d[25]), "+f"(d[26]), "+f"(d[27]), "+f"(d[28]), "+f"(d[29]), "+f"(d[30]), "+f"(d[31]), "+f"(d[32]), "+f"(d[33]), "+f"(d[34]), "+f"(d[35]), "+f"(d[36]), "+f"(d[37]), "+f"(d[38]), "+f"(d[39]), "+f"(d[40]), "+f"(d[41]), "+f"(d[42]), "+f"(d[43]), "+f"(d[44]), "+f"(d[45]), "+f"(d[46]), "+f"(d[47]), "+f"(d[48]), "+f"(d[49]), "+f"(d[50]), "+f"(d[51]), "+f"(d[52]), "+f"(d[53]), "+f"(d[54]), "+f"(d[55]), "+f"(d[56]), "+f"(d[57]), "+f"(d[58]), "+f"(d[59]), "+f"(d[60]), "+f"(d[61]), "+f"(d[62]), "+f"(d[63])
    : "r"(a0), "r"(a1), "r"(a2), "r"(a3), "l"(descB), "r"(scaleD));
}
template<int N> __device__ __forceinline__ void wgmma_ss(float* d, uint64_t descA, uint64_t descB, int scaleD);
template<> __device__ __forceinline__ void wgmma_ss<64>(float* d, uint64_t descA, uint64_t descB, int scaleD) {
  asm volatile("{\n.reg .pred p;\nsetp.ne.b32 p, %34, 0;\n"
    "wgmma.mma_async.sync.aligned.m64n64k16.f32.bf16.bf16 {%0, %1, %2, %3, %4, %5, %6, %7, %8, %9, %10, %11, %12, %13, %14, %15, %16, %17, %18, %19, %20, %21, %22, %23, %24, %25, %26, %27, %28, %29, %30, %31}, %32, %33, p, 1, 1, 0, 1;\n}\n"
    : "+f"(d[0]), "+f"(d[1]), "+f"(d[2]), "+f"(d[3]), "+f"(d[4]), "+f"(d[5]), "+f"(d[6]), "+f"(d[7]), "+f"(d[8]), "+f"(d[9]), "+f"(d[10]), "+f"(d[11]), "+f"(d[12]), "+f"(d[13]), "+f"(d[14]), "+f"(d[15]), "+f"(d[16]), "+f"(d[17]), "+f"(d[18]), "+f"(d[19]), "+f"(d[20]), "+f"(d[21]), "+f"(d[22]), "+f"(d[23]), "+f"(d[24]), "+f"(d[25]), "+f"(d[26]), "+f"(d[27]), "+f"(d[28]), "+f"(d[29]), "+f"(d[30]), "+f"(d[31])
    : "l"(descA), "l"(descB), "r"(scaleD));
}
template<> __device__ __forceinline__ void wgmma_ss<128>(float* d, uint64_t descA, uint64_t descB, int scaleD) {
  asm volatile("{\n.reg .pred p;\nsetp.ne.b32 p, %66, 0;\n"
    "wgmma.mma_async.sync.aligned.m64n128k16.f32.bf16.bf16 {%0, %1, %2, %3, %4, %5, %6, %7, %8, %9, %10, %11, %12, %13, %14, %15, %16, %17, %18, %19, %20, %21, %22, %23, %24, %25, %26, %27, %28, %29, %30, %31, %32, %33, %34, %35, %36, %37, %38, %39, %40, %41, %42, %43, %44, %45, %46, %47, %48, %49, %50, %51, %52, %53, %54, %55, %56, %57, %58, %59, %60, %61, %62, %63}, %64, %65, p, 1, 1, 0, 1;\n}\n"
    : "+f"(d[0]), "+f"(d[1]), "+f"(d[2]), "+f"(d[3]), "+f"(d[4]), "+f"(d[5]), "+f"(d[6]), "+f"(d[7]), "+f"(d[8]), "+f"(d[9]), "+f"(d[10]), "+f"(d[11]), "+f"(d[12]), "+f"(d[13]), "+f"(d[14]), "+f"(d[15]), "+f"(d[16]), "+f"(d[17]), "+f"(d[18]), "+f"(d[19]), "+f"(d[20]), "+f"(d[21]), "+f"(d[22]), "+f"(d[23]), "+f"(d[24]), "+f"(d[25]), "+f"(d[26]), "+f"(d[27]), "+f"(d[28]), "+f"(d[29]), "+f"(d[30]), "+f"(d[31]), "+f"(d[32]), "+f"(d[33]), "+f"(d[34]), "+f"(d[35]), "+f"(d[36]), "+f"(d[37]), "+f"(d[38]), "+f"(d[39]), "+f"(d[40]), "+f"(d[41]), "+f"(d[42]), "+f"(d[43]), "+f"(d[44]), "+f"(d[45]), "+f"(d[46]), "+f"(d[47]), "+f"(d[48]), "+f"(d[49]), "+f"(d[50]), "+f"(d[51]), "+f"(d[52]), "+f"(d[53]), "+f"(d[54]), "+f"(d[55]), "+f"(d[56]), "+f"(d[57]), "+f"(d[58]), "+f"(d[59]), "+f"(d[60]), "+f"(d[61]), "+f"(d[62]), "+f"(d[63])
    : "l"(descA), "l"(descB), "r"(scaleD));
}
template<> __device__ __forceinline__ void wgmma_ss<224>(float* d, uint64_t descA, uint64_t descB, int scaleD) {
  asm volatile("{\n.reg .pred p;\nsetp.ne.b32 p, %114, 0;\n"
    "wgmma.mma_async.sync.aligned.m64n224k16.f32.bf16.bf16 {%0, %1, %2, %3, %4, %5, %6, %7, %8, %9, %10, %11, %12, %13, %14, %15, %16, %17, %18, %19, %20, %21, %22, %23, %24, %25, %26, %27, %28, %29, %30, %31, %32, %33, %34, %35, %36, %37, %38, %39, %40, %41, %42, %43, %44, %45, %46, %47, %48, %49, %50, %51, %52, %53, %54, %55, %56, %57, %58, %59, %60, %61, %62, %63, %64, %65, %66, %67, %68, %69, %70, %71, %72, %73, %74, %75, %76, %77, %78, %79, %80, %81, %82, %83, %84, %85, %86, %87, %88, %89, %90, %91, %92, %93, %94, %95, %96, %97, %98, %99, %100, %101, %102, %103, %104, %105, %106, %107, %108, %109, %110, %111}, %112, %113, p, 1, 1, 0, 1;\n}\n"
    : "+f"(d[0]), "+f"(d[1]), "+f"(d[2]), "+f"(d[3]), "+f"(d[4]), "+f"(d[5]), "+f"(d[6]), "+f"(d[7]), "+f"(d[8]), "+f"(d[9]), "+f"(d[10]), "+f"(d[11]), "+f"(d[12]), "+f"(d[13]), "+f"(d[14]), "+f"(d[15]), "+f"(d[16]), "+f"(d[17]), "+f"(d[18]), "+f"(d[19]), "+f"(d[20]), "+f"(d[21]), "+f"(d[22]), "+f"(d[23]), "+f"(d[24]), "+f"(d[25]), "+f"(d[26]), "+f"(d[27]), "+f"(d[28]), "+f"(d[29]), "+f"(d[30]), "+f"(d[31]), "+f"(d[32]), "+f"(d[33]), "+f"(d[34]), "+f"(d[35]), "+f"(d[36]), "+f"(d[37]), "+f"(d[38]), "+f"(d[39]), "+f"(d[40]), "+f"(d[41]), "+f"(d[42]), "+f"(d[43]), "+f"(d[44]), "+f"(d[45]), "+f"(d[46]), "+f"(d[47]), "+f"(d[48]), "+f"(d[49]), "+f"(d[50]), "+f"(d[51]), "+f"(d[52]), "+f"(d[53]), "+f"(d[54]), "+f"(d[55]), "+f"(d[56]), "+f"(d[57]), "+f"(d[58]), "+f"(d[59]), "+f"(d[60]), "+f"(d[61]), "+f"(d[62]), "+f"(d[63]), "+f"(d[64]), "+f"(d[65]), "+f"(d[66]), "+f"(d[67]), "+f"(d[68]), "+f"(d[69]), "+f"(d[70]), "+f"(d[71]), "+f"(d[72]), "+f"(d[73]), "+f"(d[74]), "+f"(d[75]), "+f"(d[76]), "+f"(d[77]), "+f"(d[78]), "+f"(d[79]), "+f"(d[80]), "+f"(d[81]), "+f"(d[82]), "+f"(d[83]), "+f"(d[84]), "+f"(d[85]), "+f"(d[86]), "+f"(d[87]), "+f"(d[88]), "+f"(d[89]), "+f"(d[90]), "+f"(d[91]), "+f"(d[92]), "+f"(d[93]), "+f"(d[94]), "+f"(d[95]), "+f"(d[96]), "+f"(d[97]), "+f"(d[98]), "+f"(d[99]), "+f"(d[100]), "+f"(d[101]), "+f"(d[102]), "+f"(d[103]), "+f"(d[104]), "+f"(d[105]), "+f"(d[106]), "+f"(d[107]), "+f"(d[108]), "+f"(d[109]), "+f"(d[110]), "+f"(d[111])
    : "l"(descA), "l"(descB), "r"(scaleD));
}
template<> __device__ __forceinline__ void wgmma_ss<256>(float* d, uint64_t descA, uint64_t descB, int scaleD) {
  asm volatile("{\n.reg .pred p;\nsetp.ne.b32 p, %130, 0;\n"
    "wgmma.mma_async.sync.aligned.m64n256k16.f32.bf16.bf16 {%0, %1, %2, %3, %4, %5, %6, %7, %8, %9, %10, %11, %12, %13, %14, %15, %16, %17, %18, %19, %20, %21, %22, %23, %24, %25, %26, %27, %28, %29, %30, %31, %32, %33, %34, %35, %36, %37, %38, %39, %40, %41, %42, %43, %44, %45, %46, %47, %48, %49, %50, %51, %52, %53, %54, %55, %56, %57, %58, %59, %60, %61, %62, %63, %64, %65, %66, %67, %68, %69, %70, %71, %72, %73, %74, %75, %76, %77, %78, %79, %80, %81, %82, %83, %84, %85, %86, %87, %88, %89, %90, %91, %92, %93, %94, %95, %96, %97, %98, %99, %100, %101, %102, %103, %104, %105, %106, %107, %108, %109, %110, %111, %112, %113, %114, %115, %116, %117, %118, %119, %120, %121, %122, %123, %124, %125, %126, %127}, %128, %129, p, 1, 1, 0, 1;\n}\n"
    : "+f"(d[0]), "+f"(d[1]), "+f"(d[2]), "+f"(d[3]), "+f"(d[4]), "+f"(d[5]), "+f"(d[6]), "+f"(d[7]), "+f"(d[8]), "+f"(d[9]), "+f"(d[10]), "+f"(d[11]), "+f"(d[12]), "+f"(d[13]), "+f"(d[14]), "+f"(d[15]), "+f"(d[16]), "+f"(d[17]), "+f"(d[18]), "+f"(d[19]), "+f"(d[20]), "+f"(d[21]), "+f"(d[22]), "+f"(d[23]), "+f"(d[24]), "+f"(d[25]), "+f"(d[26]), "+f"(d[27]), "+f"(d[28]), "+f"(d[29]), "+f"(d[30]), "+f"(d[31]), "+f"(d[32]), "+f"(d[33]), "+f"(d[34]), "+f"(d[35]), "+f"(d[36]), "+f"(d[37]), "+f"(d[38]), "+f"(d[39]), "+f"(d[40]), "+f"(d[41]), "+f"(d[42]), "+f"(d[43]), "+f"(d[44]), "+f"(d[45]), "+f"(d[46]), "+f"(d[47]), "+f"(d[48]), "+f"(d[49]), "+f"(d[50]), "+f"(d[51]), "+f"(d[52]), "+f"(d[53]), "+f"(d[54]), "+f"(d[55]), "+f"(d[56]), "+f"(d[57]), "+f"(d[58]), "+f"(d[59]), "+f"(d[60]), "+f"(d[61]), "+f"(d[62]), "+f"(d[63]), "+f"(d[64]), "+f"(d[65]), "+f"(d[66]), "+f"(d[67]), "+f"(d[68]), "+f"(d[69]), "+f"(d[70]), "+f"(d[71]), "+f"(d[72]), "+f"(d[73]), "+f"(d[74]), "+f"(d[75]), "+f"(d[76]), "+f"(d[77]), "+f"(d[78]), "+f"(d[79]), "+f"(d[80]), "+f"(d[81]), "+f"(d[82]), "+f"(d[83]), "+f"(d[84]), "+f"(d[85]), "+f"(d[86]), "+f"(d[87]), "+f"(d[88]), "+f"(d[89]), "+f"(d[90]), "+f"(d[91]), "+f"(d[92]), "+f"(d[93]), "+f"(d[94]), "+f"(d[95]), "+f"(d[96]), "+f"(d[97]), "+f"(d[98]), "+f"(d[99]), "+f"(d[100]), "+f"(d[101]), "+f"(d[102]), "+f"(d[103]), "+f"(d[104]), "+f"(d[105]), "+f"(d[106]), "+f"(d[107]), "+f"(d[108]), "+f"(d[109]), "+f"(d[110]), "+f"(d[111]), "+f"(d[112]), "+f"(d[113]), "+f"(d[114]), "+f"(d[115]), "+f"(d[116]), "+f"(d[117]), "+f"(d[118]), "+f"(d[119]), "+f"(d[120]), "+f"(d[121]), "+f"(d[122]), "+f"(d[123]), "+f"(d[124]), "+f"(d[125]), "+f"(d[126]), "+f"(d[127])
    : "l"(descA), "l"(descB), "r"(scaleD));
}

__device__ __nv_bfloat16 g_U[DM * S_LEN];
__device__ int g_flag[16];

__global__ void __launch_bounds__(256)
kv_mod_kernel(const __nv_bfloat16* __restrict__ kin, const __nv_bfloat16* __restrict__ vin,
              const __nv_bfloat16* __restrict__ shift_k, const __nv_bfloat16* __restrict__ cvec,
              const __nv_bfloat16* __restrict__ w_mod) {
  __shared__ __align__(16) uint8_t stage[128 * 128];
  __shared__ float red[8 * 32];
  const int tid = threadIdx.x;
  TS(4, 0, tid == 0);
  pdl_launch();
  if (blockIdx.x == 0 && tid < 16) g_flag[tid] = 0;
  const int rb = blockIdx.x >> 2, cb = blockIdx.x & 3;
  const int tg = tid >> 5, cgrp = tid & 31;
  const int s0 = rb * 64 + tg * 8;
  const int dcol = cb * 128 + cgrp * 4;
  uint2 kr[11], vr[8];
#pragma unroll
  for (int i = 0; i < 11; i++) {
    int s = s0 - 3 + i;
    kr[i] = (s >= 0) ? __ldg(reinterpret_cast<const uint2*>(kin + (size_t)s * DM + dcol)) : make_uint2(0, 0);
  }
#pragma unroll
  for (int i = 0; i < 8; i++) vr[i] = __ldg(reinterpret_cast<const uint2*>(vin + (size_t)(s0 + i) * DM + dcol));
  const uint4 wa = __ldg(reinterpret_cast<const uint4*>(shift_k + dcol * 4));
  const uint4 wb = __ldg(reinterpret_cast<const uint4*>(shift_k + dcol * 4 + 8));
  const bool do_gemv = blockIdx.x < 96;
  const int vec = tid & 3, rg = tid >> 2;
  uint4 wv[8];
  unsigned short craw[8];
  if (do_gemv) {
#pragma unroll
    for (int i = 0; i < 8; i++) {
      int row = rg + 64 * i;
      wv[i] = __ldg(reinterpret_cast<const uint4*>(w_mod + (size_t)row * (6 * DM) + blockIdx.x * 32 + vec * 8));
      craw[i] = __ldg(reinterpret_cast<const unsigned short*>(cvec) + row);
    }
  }
  uint32_t W[2][4];
  W[0][0] = prmt(wa.x, wa.z, 0x5410); W[0][1] = prmt(wa.x, wa.z, 0x7632);
  W[0][2] = prmt(wa.y, wa.w, 0x5410); W[0][3] = prmt(wa.y, wa.w, 0x7632);
  W[1][0] = prmt(wb.x, wb.z, 0x5410); W[1][1] = prmt(wb.x, wb.z, 0x7632);
  W[1][2] = prmt(wb.y, wb.w, 0x5410); W[1][3] = prmt(wb.y, wb.w, 0x7632);
#pragma unroll
  for (int p = 0; p < 2; p++) {
    uint32_t kv[8];
#pragma unroll
    for (int i = 0; i < 8; i++) {
      uint32_t ks = bmul2(p ? kr[i].y : kr[i].x, W[p][3]);
      ks = badd2(ks, bmul2(p ? kr[i + 1].y : kr[i + 1].x, W[p][2]));
      ks = badd2(ks, bmul2(p ? kr[i + 2].y : kr[i + 2].x, W[p][1]));
      ks = badd2(ks, bmul2(p ? kr[i + 3].y : kr[i + 3].x, W[p][0]));
      kv[i] = bmul2(ks, p ? vr[i].y : vr[i].x);
    }
    uint4 lo, hi;
    lo.x = prmt(kv[7], kv[6], 0x5410); lo.y = prmt(kv[5], kv[4], 0x5410);
    lo.z = prmt(kv[3], kv[2], 0x5410); lo.w = prmt(kv[1], kv[0], 0x5410);
    hi.x = prmt(kv[7], kv[6], 0x7632); hi.y = prmt(kv[5], kv[4], 0x7632);
    hi.z = prmt(kv[3], kv[2], 0x7632); hi.w = prmt(kv[1], kv[0], 0x7632);
    uint8_t* dst = stage + (cgrp * 4 + 2 * p) * 128 + (1 - (tg & 1)) * 64 + (tg >> 1) * 16;
    *reinterpret_cast<uint4*>(dst) = lo;
    *reinterpret_cast<uint4*>(dst + 128) = hi;
  }
  if (do_gemv) {
    float macc[8];
#pragma unroll
    for (int e = 0; e < 8; e++) macc[e] = 0.f;
#pragma unroll
    for (int i = 0; i < 8; i++) {
      float cf = __uint_as_float((uint32_t)craw[i] << 16);
      float sc = rbf(cf / (1.0f + expf(-cf)));
      macc[0] += sc * bf_lo(wv[i].x); macc[1] += sc * bf_hi(wv[i].x);
      macc[2] += sc * bf_lo(wv[i].y); macc[3] += sc * bf_hi(wv[i].y);
      macc[4] += sc * bf_lo(wv[i].z); macc[5] += sc * bf_hi(wv[i].z);
      macc[6] += sc * bf_lo(wv[i].w); macc[7] += sc * bf_hi(wv[i].w);
    }
#pragma unroll
    for (int e = 0; e < 8; e++) {
      macc[e] += __shfl_xor_sync(0xffffffffu, macc[e], 4);
      macc[e] += __shfl_xor_sync(0xffffffffu, macc[e], 8);
      macc[e] += __shfl_xor_sync(0xffffffffu, macc[e], 16);
    }
    if ((tid & 31) < 4) {
      *reinterpret_cast<float4*>(red + (tid >> 5) * 32 + vec * 8) = make_float4(macc[0], macc[1], macc[2], macc[3]);
      *reinterpret_cast<float4*>(red + (tid >> 5) * 32 + vec * 8 + 4) = make_float4(macc[4], macc[5], macc[6], macc[7]);
    }
  }
  __syncthreads();
#pragma unroll
  for (int i = 0; i < 4; i++) {
    const int v = tid + 256 * i;
    const int ch = v >> 3, pl = (v >> 2) & 1, ck = v & 3;
    const uint4 x = *reinterpret_cast<const uint4*>(stage + v * 16);
    *reinterpret_cast<uint4*>(g_U + (size_t)(cb * 128 + ch) * S_LEN + pl * 1024 + (rb * 4 + ck) * 8) = x;
  }
  if (do_gemv && tid < 32) {
    float s = 0.f;
#pragma unroll
    for (int w = 0; w < 8; w++) s += red[w * 32 + tid];
    g_mod[blockIdx.x * 32 + tid] = __float2bfloat16_rn(s);
  }
  TS(4, 1, tid == 0);
}

constexpr int K1_THREADS = 512;
constexpr int U_ROWS  = 136;
constexpr int U_PLANE = U_ROWS * 16;
constexpr int U_CH    = 2 * U_PLANE;
constexpr int F_LEN   = 2048 + 32;
constexpr int F_COPY  = F_LEN * 2;
constexpr int F_CH    = 2 * F_COPY;
constexpr int P_CH    = 4 * 2048 * 4;
constexpr int K1_OFF_U = 0;
constexpr int K1_OFF_F = K1_OFF_U + 4 * U_CH;
constexpr int K1_OFF_P = K1_OFF_F + 4 * F_CH;
constexpr int K1_SMEM  = K1_OFF_P + 4 * P_CH;

template <int T> struct ConvStep {
  static __device__ __forceinline__ void run(float* acc, const uint32_t* fp, uint64_t d0, uint64_t d1) {
    constexpr int N = 128 - 8 * T;
    uint32_t a0 = fp[64 * T], a1 = fp[64 * T + 4], a3 = fp[64 * T + 8];
    uint32_t b0 = fp[64 * T + 32], b1 = fp[64 * T + 36], b3 = fp[64 * T + 40];
    wgmma_fence();
    wgmma_rs<N>(acc + 4 * T, a0, a1, a1, a3, d0, T == 0 ? 0 : 1);
    wgmma_rs<N>(acc + 4 * T, b0, b1, b1, b3, d1, 1);
    wgmma_commit();
    wgmma_wait<0>();
    asm volatile("" ::"r"(a0), "r"(a1), "r"(a3), "r"(b0), "r"(b1), "r"(b3));
    ConvStep<T + 1>::run(acc, fp, d0, d1);
  }
};
template <> struct ConvStep<16> {
  static __device__ __forceinline__ void run(float*, const uint32_t*, uint64_t, uint64_t) {}
};

__global__ void __launch_bounds__(K1_THREADS, 1)
conv_kernel(const __nv_bfloat16* __restrict__ ssm_k, const __nv_bfloat16* __restrict__ ssm_D) {
  extern __shared__ __align__(1024) uint8_t smem[];
  __shared__ __align__(8) uint64_t ubar;
  const int tid = threadIdx.x;
  const int d0 = blockIdx.x * 4;
  TS(0, 0, tid == 0);
  pdl_launch();
  if (tid == 0) {
    asm volatile("mbarrier.init.shared::cta.b64 [%0], 1;" ::"r"(smem_u32(&ubar)) : "memory");
    asm volatile("fence.mbarrier_init.release.cluster;" ::: "memory");
    asm volatile("fence.proxy.async;" ::: "memory");
  }
  const uint2 dr = __ldg(reinterpret_cast<const uint2*>(ssm_D + d0));
  {
    uint4 fv[2];
    uint32_t fx[2];
    const int j = tid & 255;
#pragma unroll
    for (int i = 0; i < 2; i++) {
      const int c = (tid >> 8) * 2 + i;
      const __nv_bfloat16* fr = ssm_k + (size_t)(d0 + c) * S_LEN;
      fv[i] = __ldg(reinterpret_cast<const uint4*>(fr + 8 * j));
      fx[i] = (j < 255) ? (uint32_t)__ldg(reinterpret_cast<const unsigned short*>(fr + 8 * j + 8)) : 0u;
    }
    if (tid == 32) {
      pdl_wait();
      const uint32_t bar = smem_u32(&ubar);
      asm volatile("mbarrier.arrive.expect_tx.shared::cta.b64 _, [%0], %1;" ::"r"(bar), "r"(4 * 4096) : "memory");
#pragma unroll
      for (int c = 0; c < 4; c++)
#pragma unroll
        for (int pl = 0; pl < 2; pl++)
          asm volatile("cp.async.bulk.shared::cluster.global.mbarrier::complete_tx::bytes [%0], [%1], %2, [%3];"
                       ::"r"(smem_u32(smem + K1_OFF_U + c * U_CH + pl * U_PLANE + 8 * 16)),
                         "l"(g_U + (size_t)(d0 + c) * S_LEN + pl * 1024), "r"(2048), "r"(bar) : "memory");
    }
#pragma unroll
    for (int i = 0; i < 2; i++) {
      const int c = (tid >> 8) * 2 + i;
      uint8_t* f0 = smem + K1_OFF_F + c * F_CH;
      uint8_t* f1 = f0 + F_COPY;
      *reinterpret_cast<uint4*>(f0 + 32 + 16 * j) = fv[i];
      uint4 sh;
      sh.x = __funnelshift_r(fv[i].x, fv[i].y, 16);
      sh.y = __funnelshift_r(fv[i].y, fv[i].z, 16);
      sh.z = __funnelshift_r(fv[i].z, fv[i].w, 16);
      sh.w = __funnelshift_r(fv[i].w, fx[i], 16);
      *reinterpret_cast<uint4*>(f1 + 32 + 16 * j) = sh;
      if (j == 0) {
        *reinterpret_cast<uint4*>(f0) = make_uint4(0, 0, 0, 0);
        *reinterpret_cast<uint4*>(f0 + 16) = make_uint4(0, 0, 0, 0);
        *reinterpret_cast<uint4*>(f1) = make_uint4(0, 0, 0, 0);
        *reinterpret_cast<uint4*>(f1 + 16) = make_uint4(0, 0, 0, fv[i].x << 16);
      }
      if (j == 1) {
        *reinterpret_cast<uint4*>(f0 + 32 + 4096) = make_uint4(0, 0, 0, 0);
        *reinterpret_cast<uint4*>(f0 + 32 + 4096 + 16) = make_uint4(0, 0, 0, 0);
        *reinterpret_cast<uint4*>(f1 + 32 + 4096) = make_uint4(0, 0, 0, 0);
        *reinterpret_cast<uint4*>(f1 + 32 + 4096 + 16) = make_uint4(0, 0, 0, 0);
      }
    }
    if (tid >= 64 && tid < 128) {
      int q = tid - 64, c = q >> 4, pl = (q >> 3) & 1, r = q & 7;
      *reinterpret_cast<uint4*>(smem + K1_OFF_U + c * U_CH + pl * U_PLANE + r * 16) = make_uint4(0, 0, 0, 0);
    }
  }
  TS(0, 1, tid == 0);
  fence_proxy_async();
  __syncthreads();
  {
    const uint32_t bar = smem_u32(&ubar);
    asm volatile(
        "{\n.reg .pred p;\n"
        "K1_WAIT:\n"
        "mbarrier.try_wait.parity.shared::cta.b64 p, [%0], 0, 0x989680;\n"
        "@p bra K1_DONE;\n"
        "bra K1_WAIT;\n"
        "K1_DONE:\n}\n" ::"r"(bar) : "memory");
  }
  TS(0, 2, tid == 0);

  const int warp = tid >> 5, lane = tid & 31;
  const int c = warp >> 2, w = warp & 3;
  const int g8 = lane >> 2, t4 = lane & 3;
  {
    const int x0 = 16 * w + g8 + 2 * t4 - 15;
    const int par = x0 & 1;
    const uint32_t* fp = reinterpret_cast<const uint32_t*>(smem + K1_OFF_F + c * F_CH + par * F_COPY) + ((16 + x0 - par) >> 1);
    float acc[64];
    const uint32_t ubase = smem_u32(smem + K1_OFF_U + c * U_CH);
    const uint64_t dsc0 = make_desc(ubase + 8 * 16, U_PLANE, 128, 0);
    const uint64_t dsc1 = make_desc(ubase + 4 * 16, U_PLANE, 128, 0);
    ConvStep<0>::run(acc, fp, dsc0, dsc1);
    TS(0, 3, tid == 0);
    float* P = reinterpret_cast<float*>(smem + K1_OFF_P + c * P_CH) + w * 2048 + t4 * 32;
#pragma unroll
    for (int jj = 0; jj < 16; jj++) {
#pragma unroll
      for (int e = 0; e < 2; e++) {
#pragma unroll
        for (int hi = 0; hi < 2; hi++) {
          int col = (16 * e + g8 + 8 * hi) ^ (8 * t4);
          P[jj * 128 + col] = acc[4 * jj + e + 2 * hi];
        }
      }
    }
  }
  __syncthreads();
  TS(0, 4, tid == 0);

  {
    const int s = 4 * tid;
    uint32_t ylo[4], yhi[4];
#pragma unroll
    for (int cc = 0; cc < 4; cc++) {
      const float* P = reinterpret_cast<const float*>(smem + K1_OFF_P + cc * P_CH);
      float4 sum = make_float4(0.f, 0.f, 0.f, 0.f);
#pragma unroll
      for (int ww = 0; ww < 4; ww++) {
        int sp = s - 16 * ww;
        if (sp >= 0) {
          int aa = sp >> 4, rr = sp & 15;
          int col = (16 * (aa & 1) + rr) ^ (8 * ((aa >> 1) & 3));
          float4 v = *reinterpret_cast<const float4*>(P + ww * 2048 + (aa >> 1) * 32 + col);
          sum.x += v.x; sum.y += v.y; sum.z += v.z; sum.w += v.w;
        }
      }
      const int kidx = 15 - (s & 15);
      const uint8_t* up = smem + K1_OFF_U + cc * U_CH + (kidx >> 3) * U_PLANE + ((s >> 4) + 8) * 16 + ((kidx & 7) - 3) * 2;
      const uint2 kvr = *reinterpret_cast<const uint2*>(up);
      const uint32_t kv01 = prmt(kvr.y, kvr.y, 0x1032);
      const uint32_t kv23 = prmt(kvr.x, kvr.x, 0x1032);
      const uint32_t dcc = (cc & 1) ? prmt(cc < 2 ? dr.x : dr.y, 0, 0x3232) : prmt(cc < 2 ? dr.x : dr.y, 0, 0x1010);
      ylo[cc] = badd2(pack_bf(sum.x, sum.y), bmul2(kv01, dcc));
      yhi[cc] = badd2(pack_bf(sum.z, sum.w), bmul2(kv23, dcc));
    }
    uint4 o0, o1;
    o0.x = prmt(ylo[0], ylo[1], 0x5410); o0.y = prmt(ylo[2], ylo[3], 0x5410);
    o0.z = prmt(ylo[0], ylo[1], 0x7632); o0.w = prmt(ylo[2], ylo[3], 0x7632);
    o1.x = prmt(yhi[0], yhi[1], 0x5410); o1.y = prmt(yhi[2], yhi[3], 0x5410);
    o1.z = prmt(yhi[0], yhi[1], 0x7632); o1.w = prmt(yhi[2], yhi[3], 0x7632);
    uint4* yo = reinterpret_cast<uint4*>(g_yt + ((size_t)blockIdx.x * S_LEN + s) * 4);
    yo[0] = o0;
    yo[1] = o1;
  }
  TS(0, 5, tid == 0);
}

__device__ __forceinline__ void row_stats(const uint32_t* x, float& mb, float& rden) {
  float f[16];
#pragma unroll
  for (int i = 0; i < 8; i++) { f[2 * i] = bf_lo(x[i]); f[2 * i + 1] = bf_hi(x[i]); }
  float s0 = 0.f, s1 = 0.f;
#pragma unroll
  for (int i = 0; i < 8; i++) { s0 += f[2 * i]; s1 += f[2 * i + 1]; }
  float sum = s0 + s1;
#pragma unroll
  for (int o = 16; o > 0; o >>= 1) sum += __shfl_xor_sync(0xffffffffu, sum, o);
  const float mean = sum * (1.0f / DM);
  s0 = 0.f; s1 = 0.f;
#pragma unroll
  for (int i = 0; i < 8; i++) {
    float d0 = f[2 * i] - mean, d1 = f[2 * i + 1] - mean;
    s0 += d0 * d0; s1 += d1 * d1;
  }
  float vs = s0 + s1;
#pragma unroll
  for (int o = 16; o > 0; o >>= 1) vs += __shfl_xor_sync(0xffffffffu, vs, o);
  mb = rbf(mean);
  const float den = rbf(sqrtf(rbf(rbf(vs * (1.0f / DM)) + 1e-5f)));
  rden = 1.0f / den;
}
__device__ __forceinline__ uint32_t normalize2(uint32_t x2, uint32_t mb2, float rden) {
  const uint32_t xm = bsub2(x2, mb2);
  return pack_bf(bf_lo(xm) * rden, bf_hi(xm) * rden);
}

__global__ void __launch_bounds__(256) ln_kernel(const __nv_bfloat16* __restrict__ q) {
  __shared__ __align__(16) uint8_t ysm[128 * 128];
  const int tid = threadIdx.x, warp = tid >> 5, lane = tid & 31;
  const int r0 = blockIdx.x * 16;
  TS(1, 0, threadIdx.x == 0);
  pdl_launch();
  uint32_t x[2][8];
  float mb[2], rden[2];
#pragma unroll
  for (int rr = 0; rr < 2; rr++) {
    const int s = r0 + warp * 2 + rr;
    uint4 qa = __ldg(reinterpret_cast<const uint4*>(q + (size_t)s * DM + lane * 8));
    uint4 qb = __ldg(reinterpret_cast<const uint4*>(q + (size_t)s * DM + 256 + lane * 8));
    x[rr][0] = qa.x; x[rr][1] = qa.y; x[rr][2] = qa.z; x[rr][3] = qa.w;
    x[rr][4] = qb.x; x[rr][5] = qb.y; x[rr][6] = qb.z; x[rr][7] = qb.w;
  }
#pragma unroll 1
  for (int rr = 0; rr < 2; rr++) row_stats(x[rr], mb[rr], rden[rr]);
  uint32_t md[5][8];
#pragma unroll
  for (int m = 0; m < 5; m++)
#pragma unroll
    for (int i = 0; i < 8; i++) md[m][i] = 0;
  const uint32_t ONE2 = 0x3f803f80u;
#pragma unroll 1
  for (int pass = 0; pass < 3; pass++) {
    if (pass == 1) {
      pdl_wait();
      TS(1, 1, threadIdx.x == 0);
      uint4 yv[4];
#pragma unroll
      for (int i = 0; i < 4; i++) {
        const int v = tid + 256 * i;
        yv[i] = *reinterpret_cast<const uint4*>(g_yt + ((size_t)(v >> 3) * S_LEN + r0) * 4 + (v & 7) * 8);
      }
#pragma unroll
      for (int m = 0; m < 5; m++) {
        uint4 a = *reinterpret_cast<const uint4*>(g_mod + m * DM + lane * 8);
        uint4 b = *reinterpret_cast<const uint4*>(g_mod + m * DM + 256 + lane * 8);
        md[m][0] = a.x; md[m][1] = a.y; md[m][2] = a.z; md[m][3] = a.w;
        md[m][4] = b.x; md[m][5] = b.y; md[m][6] = b.z; md[m][7] = b.w;
      }
#pragma unroll
      for (int i = 0; i < 4; i++) *reinterpret_cast<uint4*>(ysm + (tid + 256 * i) * 16) = yv[i];
      __syncthreads();
    }
    const int rr = (pass == 2) ? 1 : 0;
    const int row = warp * 2 + rr, s = r0 + row;
    uint32_t xr[8];
#pragma unroll
    for (int i = 0; i < 8; i++) xr[i] = rr ? x[1][i] : x[0][i];
    const float mbr = rr ? mb[1] : mb[0], rdr = rr ? rden[1] : rden[0];
    uint32_t yt[8];
#pragma unroll
    for (int b = 0; b < 4; b++) {
      const int blk = (b < 2) ? (2 * lane + b) : (64 + 2 * lane + (b - 2));
      const uint2 y = *reinterpret_cast<const uint2*>(ysm + blk * 128 + row * 8);
      yt[2 * b] = y.x; yt[2 * b + 1] = y.y;
    }
    if (pass == 1) TS(1, 6, threadIdx.x == 0);
    uint32_t mb2 = pack_bf(mbr, mbr);
    uint32_t x1[8];
#pragma unroll
    for (int i = 0; i < 8; i++) {
      uint32_t ln = normalize2(xr[i], mb2, rdr);
      uint32_t h = badd2(bmul2(ln, badd2(ONE2, md[1][i])), md[0][i]);
      uint32_t av = bmul2(h, yt[i]);
      x1[i] = badd2(xr[i], bmul2(md[2][i], av));
    }
    float mb_2, rden_2;
    if (pass == 1) TS(1, 7, threadIdx.x == 0);
    row_stats(x1, mb_2, rden_2);
    if (pass == 1) TS(1, 8, threadIdx.x == 0);
    mb2 = pack_bf(mb_2, mb_2);
    uint32_t h2[8];
#pragma unroll
    for (int i = 0; i < 8; i++) {
      uint32_t ln = normalize2(x1[i], mb2, rden_2);
      h2[i] = badd2(bmul2(ln, badd2(ONE2, md[4][i])), md[3][i]);
    }
    if (pass == 1) TS(1, 9, threadIdx.x == 0);
    if (pass > 0) {
      *reinterpret_cast<uint4*>(g_x1 + (size_t)s * DM + lane * 8) = make_uint4(x1[0], x1[1], x1[2], x1[3]);
      *reinterpret_cast<uint4*>(g_x1 + (size_t)s * DM + 256 + lane * 8) = make_uint4(x1[4], x1[5], x1[6], x1[7]);
      *reinterpret_cast<uint4*>(g_h2 + (size_t)s * DM + lane * 8) = make_uint4(h2[0], h2[1], h2[2], h2[3]);
      *reinterpret_cast<uint4*>(g_h2 + (size_t)s * DM + 256 + lane * 8) = make_uint4(h2[4], h2[5], h2[6], h2[7]);
    }
    if (pass == 1) TS(1, 5, threadIdx.x == 0);
  }
  TS(1, 2, threadIdx.x == 0);
}

__device__ __forceinline__ uint32_t mapa(uint32_t addr, uint32_t rank) {
  uint32_t r; asm("mapa.shared::cluster.u32 %0, %1, %2;" : "=r"(r) : "r"(addr), "r"(rank)); return r; }
__device__ __forceinline__ void st_cluster_v4(uint32_t addr, uint4 v) {
  asm volatile("st.shared::cluster.v4.b32 [%0], {%1, %2, %3, %4};" ::"r"(addr), "r"(v.x), "r"(v.y), "r"(v.z), "r"(v.w) : "memory"); }
__device__ __forceinline__ void mbar_init(uint32_t bar, uint32_t count) {
  asm volatile("mbarrier.init.shared::cta.b64 [%0], %1;" ::"r"(bar), "r"(count) : "memory");
}
__device__ __forceinline__ void mbar_expect_tx(uint32_t bar, uint32_t bytes) {
  asm volatile("mbarrier.arrive.expect_tx.shared::cta.b64 _, [%0], %1;" ::"r"(bar), "r"(bytes) : "memory");
}
__device__ __forceinline__ void mbar_arrive(uint32_t bar) {
  asm volatile("mbarrier.arrive.shared::cta.b64 _, [%0];" ::"r"(bar) : "memory");
}
__device__ __forceinline__ void mbar_wait(uint32_t bar, uint32_t parity) {
  asm volatile(
      "{\n.reg .pred p;\n"
      "WAIT_LOOP:\n"
      "mbarrier.try_wait.parity.shared::cta.b64 p, [%0], %1, 0x989680;\n"
      "@p bra WAIT_DONE;\n"
      "bra WAIT_LOOP;\n"
      "WAIT_DONE:\n}\n" ::"r"(bar), "r"(parity) : "memory");
}
__device__ __forceinline__ void tma_load_2d(uint32_t dst, const CUtensorMap* tm, uint32_t bar, int c0, int c1) {
  asm volatile(
      "cp.async.bulk.tensor.2d.shared::cluster.global.mbarrier::complete_tx::bytes [%0], [%1, {%3, %4}], [%2];"
      ::"r"(dst), "l"(reinterpret_cast<uint64_t>(tm)), "r"(bar), "r"(c0), "r"(c1) : "memory");
}

__device__ __forceinline__ void tma_load_2d_mc(uint32_t dst, const CUtensorMap* tm, uint32_t bar, int c0, int c1, uint16_t mask) {
  asm volatile(
      "cp.async.bulk.tensor.2d.shared::cluster.global.mbarrier::complete_tx::bytes.multicast::cluster [%0], [%1, {%3, %4}], [%2], %5;"
      ::"r"(dst), "l"(reinterpret_cast<uint64_t>(tm)), "r"(bar), "r"(c0), "r"(c1), "h"(mask) : "memory");
}
__device__ __forceinline__ void mbar_arrive_remote(uint32_t bar, uint32_t rank) {
  asm volatile("{\n.reg .b32 ra;\nmapa.shared::cluster.u32 ra, %0, %1;\nmbarrier.arrive.shared::cluster.b64 _, [ra];\n}\n"
               ::"r"(bar), "r"(rank) : "memory");
}
__device__ __forceinline__ void ln_rows(const __nv_bfloat16* __restrict__ q, int s_first, int s_end, int lane,
                                        const uint8_t* ysm, int s_base) {
  uint32_t x[3][8], yt[3][8], md[5][8];
#pragma unroll
  for (int k = 0; k < 3; k++) {
    const int s = s_first + 8 * k;
    if (s < s_end) {
      uint4 qa = __ldg(reinterpret_cast<const uint4*>(q + (size_t)s * DM + lane * 8));
      uint4 qb = __ldg(reinterpret_cast<const uint4*>(q + (size_t)s * DM + 256 + lane * 8));
      x[k][0] = qa.x; x[k][1] = qa.y; x[k][2] = qa.z; x[k][3] = qa.w;
      x[k][4] = qb.x; x[k][5] = qb.y; x[k][6] = qb.z; x[k][7] = qb.w;
#pragma unroll
      for (int b = 0; b < 4; b++) {
        const int blk = (b < 2) ? (2 * lane + b) : (64 + 2 * lane + (b - 2));
        const uint2 y = *reinterpret_cast<const uint2*>(ysm + blk * 176 + (s - s_base) * 8);
        yt[k][2 * b] = y.x; yt[k][2 * b + 1] = y.y;
      }
    }
  }
#pragma unroll
  for (int m = 0; m < 5; m++) {
    uint4 a = *reinterpret_cast<const uint4*>(g_mod + m * DM + lane * 8);
    uint4 b = *reinterpret_cast<const uint4*>(g_mod + m * DM + 256 + lane * 8);
    md[m][0] = a.x; md[m][1] = a.y; md[m][2] = a.z; md[m][3] = a.w;
    md[m][4] = b.x; md[m][5] = b.y; md[m][6] = b.z; md[m][7] = b.w;
  }
  const uint32_t ONE2 = 0x3f803f80u;
  float mb[3], rden[3];
#pragma unroll
  for (int k = 0; k < 3; k++) row_stats(x[k], mb[k], rden[k]);
  uint32_t x1[3][8];
#pragma unroll
  for (int k = 0; k < 3; k++) {
    const uint32_t mb2 = pack_bf(mb[k], mb[k]);
#pragma unroll
    for (int i = 0; i < 8; i++) {
      uint32_t ln = normalize2(x[k][i], mb2, rden[k]);
      uint32_t h = badd2(bmul2(ln, badd2(ONE2, md[1][i])), md[0][i]);
      uint32_t av = bmul2(h, yt[k][i]);
      x1[k][i] = badd2(x[k][i], bmul2(md[2][i], av));
    }
  }
#pragma unroll
  for (int k = 0; k < 3; k++) row_stats(x1[k], mb[k], rden[k]);
#pragma unroll
  for (int k = 0; k < 3; k++) {
    const int s = s_first + 8 * k;
    const uint32_t mb2 = pack_bf(mb[k], mb[k]);
    uint32_t h2[8];
#pragma unroll
    for (int i = 0; i < 8; i++) {
      uint32_t ln = normalize2(x1[k][i], mb2, rden[k]);
      h2[i] = badd2(bmul2(ln, badd2(ONE2, md[4][i])), md[3][i]);
    }
    if (s < s_end) {
      *reinterpret_cast<uint4*>(g_x1 + (size_t)s * DM + lane * 8) = make_uint4(x1[k][0], x1[k][1], x1[k][2], x1[k][3]);
      *reinterpret_cast<uint4*>(g_x1 + (size_t)s * DM + 256 + lane * 8) = make_uint4(x1[k][4], x1[k][5], x1[k][6], x1[k][7]);
      *reinterpret_cast<uint4*>(g_h2 + (size_t)s * DM + lane * 8) = make_uint4(h2[0], h2[1], h2[2], h2[3]);
      *reinterpret_cast<uint4*>(g_h2 + (size_t)s * DM + 256 + lane * 8) = make_uint4(h2[4], h2[5], h2[6], h2[7]);
    }
  }
}

template <int BN, int STAGES, int EPI, int CL>
__global__ void __launch_bounds__(384, 1)
gemm_kernel(const __grid_constant__ CUtensorMap tmA, const __grid_constant__ CUtensorMap tmB, int K,
            __nv_bfloat16* __restrict__ outp, int ldo, const __nv_bfloat16* __restrict__ q) {
  constexpr int A_BYTES = 128 * 64 * 2;
  constexpr int B_BYTES = BN * 64 * 2;
  constexpr int STAGE_BYTES = A_BYTES + B_BYTES;
  extern __shared__ __align__(1024) uint8_t smem[];
  __shared__ __align__(8) uint64_t bars[2 * STAGES];
  const int tid = threadIdx.x, warp = tid >> 5, lane = tid & 31;
  const int m0 = blockIdx.y * 128, n0 = blockIdx.x * BN;
  const uint32_t sbase = smem_u32(smem);
  const uint32_t full0 = smem_u32(&bars[0]), empty0 = smem_u32(&bars[STAGES]);
  TS(2 + EPI, 0, tid == 0);
  pdl_launch();
  if (tid == 0) {
    for (int i = 0; i < STAGES; i++) { mbar_init(full0 + 8 * i, 1); mbar_init(empty0 + 8 * i, 2 * CL); }
    asm volatile("fence.mbarrier_init.release.cluster;" ::: "memory");
  }
  if (CL > 1) {
    asm volatile("barrier.cluster.arrive.release.aligned;" ::: "memory");
    asm volatile("barrier.cluster.wait.acquire.aligned;" ::: "memory");
  } else {
    __syncthreads();
  }
  const int nkb = K / 64;
  if (warp >= 8) {
    if (warp == 8 && lane == 0) {
      for (int kb = 0; kb < STAGES; kb++) {
        mbar_expect_tx(full0 + 8 * kb, STAGE_BYTES);
#pragma unroll
        for (int nb = 0; nb < BN / 64; nb++)
          tma_load_2d(sbase + kb * STAGE_BYTES + A_BYTES + nb * 8192, &tmB, full0 + 8 * kb, n0 + nb * 64, kb * 64);
      }
      pdl_wait();
      TS(2 + EPI, 8, true);
      for (int kb = 0; kb < STAGES; kb++) tma_load_2d(sbase + kb * STAGE_BYTES, &tmA, full0 + 8 * kb, kb * 64, m0);
      for (int kb = STAGES; kb < nkb; kb++) {
        const int st = kb % STAGES;
        mbar_wait(empty0 + 8 * st, ((kb / STAGES) & 1) ^ 1);
        mbar_expect_tx(full0 + 8 * st, STAGE_BYTES);
        const uint32_t sa = sbase + st * STAGE_BYTES;
        if (CL == 1) {
          tma_load_2d(sa, &tmA, full0 + 8 * st, kb * 64, m0);
        } else {
          const uint32_t rank = blockIdx.x & (CL - 1);
          tma_load_2d_mc(sa + rank * (A_BYTES / CL), &tmA, full0 + 8 * st, kb * 64, m0 + rank * (128 / CL), (uint16_t)((1 << CL) - 1));
        }
#pragma unroll
        for (int nb = 0; nb < BN / 64; nb++)
          tma_load_2d(sa + A_BYTES + nb * 8192, &tmB, full0 + 8 * st, n0 + nb * 64, kb * 64);
      }
    }
  } else {
    const int wg = warp >> 2;
    float acc[BN / 2];
    for (int kb = 0; kb < nkb; kb++) {
      const int st = kb % STAGES;
      mbar_wait(full0 + 8 * st, (kb / STAGES) & 1);
      if (kb == 0) TS(2 + EPI, 2, tid == 0);
      const uint32_t sa = sbase + st * STAGE_BYTES;
      wgmma_fence();
#pragma unroll
      for (int k = 0; k < 4; k++) {
        uint64_t dA = make_desc(sa + wg * 8192 + k * 32, 16, 1024, 1);
        uint64_t dB = make_desc(sa + A_BYTES + k * 2048, 8192, 1024, 1);
        wgmma_ss<BN>(acc, dA, dB, (kb > 0 || k > 0) ? 1 : 0);
      }
      wgmma_commit();
      if (kb > 0) {
        wgmma_wait<1>();
        if ((tid & 127) == 0) {
          if (CL == 1) mbar_arrive(empty0 + 8 * ((kb - 1) % STAGES));
          else {
#pragma unroll
            for (int r = 0; r < CL; r++) mbar_arrive_remote(empty0 + 8 * ((kb - 1) % STAGES), r);
          }
        }
      }
    }
    wgmma_wait<0>();
    TS(2 + EPI, 3, tid == 0);
    asm volatile("bar.sync 1, 256;" ::: "memory");
    constexpr int ROWB = BN * 2 + 16;
    uint8_t* stg = smem + wg * (64 * ROWB);
    const int w4 = warp & 3, g8 = lane >> 2, t4 = lane & 3;
#pragma unroll
    for (int j = 0; j < BN / 8; j++) {
      uint32_t p01 = pack_bf(acc[4 * j], acc[4 * j + 1]);
      uint32_t p23 = pack_bf(acc[4 * j + 2], acc[4 * j + 3]);
      if (EPI == 0) {
        p01 = pack_bf(fast_silu(bf_lo(p01)), fast_silu(bf_hi(p01)));
        p23 = pack_bf(fast_silu(bf_lo(p23)), fast_silu(bf_hi(p23)));
      } else {
        const uint32_t gb = *reinterpret_cast<const uint32_t*>(g_mod + 5 * DM + n0 + 8 * j + 2 * t4);
        p01 = bmul2(gb, p01);
        p23 = bmul2(gb, p23);
      }
      *reinterpret_cast<uint32_t*>(stg + (16 * w4 + g8) * ROWB + (8 * j + 2 * t4) * 2) = p01;
      *reinterpret_cast<uint32_t*>(stg + (16 * w4 + g8 + 8) * ROWB + (8 * j + 2 * t4) * 2) = p23;
    }
    asm volatile("bar.sync %0, 128;" ::"r"(2 + wg) : "memory");
    TS(2 + EPI, 4, tid == 0);
    constexpr int VEC_PER_ROW = BN / 8;
    const int t = tid & 127;
#pragma unroll 4
    for (int idx = t; idx < 64 * VEC_PER_ROW; idx += 128) {
      const int r = idx / VEC_PER_ROW, cv = idx % VEC_PER_ROW;
      uint4 v = *reinterpret_cast<const uint4*>(stg + r * ROWB + cv * 16);
      const size_t goff = (size_t)(m0 + wg * 64 + r) * ldo + n0 + cv * 8;
      if (EPI == 1) {
        uint4 xr = *reinterpret_cast<const uint4*>(g_x1 + goff);
        v.x = badd2(xr.x, v.x); v.y = badd2(xr.y, v.y); v.z = badd2(xr.z, v.z); v.w = badd2(xr.w, v.w);
      }
      *reinterpret_cast<uint4*>(outp + goff) = v;
    }
    TS(2 + EPI, 5, tid == 0);
  }
  if (CL > 1) {
    asm volatile("barrier.cluster.arrive.release.aligned;" ::: "memory");
    asm volatile("barrier.cluster.wait.acquire.aligned;" ::: "memory");
  }
}

constexpr int G2_STAGES = 8;
constexpr int G2_STAGE_BYTES = 8192 + 16384;
constexpr int G2_SMEM = G2_STAGES * G2_STAGE_BYTES;

__global__ void __launch_bounds__(256, 1)
gemm2_kernel(const __grid_constant__ CUtensorMap tmA, const __grid_constant__ CUtensorMap tmB,
             __nv_bfloat16* __restrict__ outp) {
  extern __shared__ __align__(1024) uint8_t smem[];
  __shared__ __align__(8) uint64_t bars[2 * G2_STAGES];
  const int tid = threadIdx.x, warp = tid >> 5, lane = tid & 31;
  const int m0 = blockIdx.y * 64, n0 = blockIdx.x * 128;
  const uint32_t sbase = smem_u32(smem);
  const uint32_t full0 = smem_u32(&bars[0]), empty0 = smem_u32(&bars[G2_STAGES]);
  TS(3, 0, tid == 0);
  pdl_launch();
  if (tid == 0) {
    for (int i = 0; i < G2_STAGES; i++) { mbar_init(full0 + 8 * i, 1); mbar_init(empty0 + 8 * i, 1); }
    asm volatile("fence.mbarrier_init.release.cluster;" ::: "memory");
  }
  __syncthreads();
  constexpr int NKB = FF / 64;
  if (warp >= 4) {
    if (warp == 4 && lane == 0) {
      for (int kb = 0; kb < G2_STAGES; kb++) {
        mbar_expect_tx(full0 + 8 * kb, G2_STAGE_BYTES);
        const uint32_t sa = sbase + kb * G2_STAGE_BYTES;
        tma_load_2d(sa + 8192, &tmB, full0 + 8 * kb, n0, kb * 64);
        tma_load_2d(sa + 8192 + 8192, &tmB, full0 + 8 * kb, n0 + 64, kb * 64);
      }
      pdl_wait();
      TS(3, 8, true);
      for (int kb = 0; kb < G2_STAGES; kb++) tma_load_2d(sbase + kb * G2_STAGE_BYTES, &tmA, full0 + 8 * kb, kb * 64, m0);
      for (int kb = G2_STAGES; kb < NKB; kb++) {
        const int st = kb % G2_STAGES;
        mbar_wait(empty0 + 8 * st, ((kb / G2_STAGES) & 1) ^ 1);
        mbar_expect_tx(full0 + 8 * st, G2_STAGE_BYTES);
        const uint32_t sa = sbase + st * G2_STAGE_BYTES;
        tma_load_2d(sa, &tmA, full0 + 8 * st, kb * 64, m0);
        tma_load_2d(sa + 8192, &tmB, full0 + 8 * st, n0, kb * 64);
        tma_load_2d(sa + 8192 + 8192, &tmB, full0 + 8 * st, n0 + 64, kb * 64);
      }
    }
  } else {
    const int t = tid;
    float acc[64];
    uint4 xpre[8];
    pdl_wait();
#pragma unroll
    for (int i = 0; i < 8; i++) {
      const int idx = t + 128 * i;
      xpre[i] = *reinterpret_cast<const uint4*>(g_x1 + (size_t)(m0 + (idx >> 4)) * DM + n0 + (idx & 15) * 8);
    }
    for (int kb = 0; kb < NKB; kb++) {
      const int st = kb % G2_STAGES;
      mbar_wait(full0 + 8 * st, (kb / G2_STAGES) & 1);
      if (kb == 0) TS(3, 2, tid == 0);
      const uint32_t sa = sbase + st * G2_STAGE_BYTES;
      wgmma_fence();
#pragma unroll
      for (int k = 0; k < 4; k++) {
        uint64_t dA = make_desc(sa + k * 32, 16, 1024, 1);
        uint64_t dB = make_desc(sa + 8192 + k * 2048, 8192, 1024, 1);
        wgmma_ss<128>(acc, dA, dB, (kb > 0 || k > 0) ? 1 : 0);
      }
      wgmma_commit();
      if (kb > 0) {
        wgmma_wait<1>();
        if (t == 0) mbar_arrive(empty0 + 8 * ((kb - 1) % G2_STAGES));
      }
    }
    wgmma_wait<0>();
    TS(3, 3, tid == 0);
    const int w4 = warp & 3, g8 = lane >> 2, t4 = lane & 3;
    constexpr int ROWB = 128 * 2 + 16;
    uint8_t* stg = smem;
#pragma unroll
    for (int j = 0; j < 16; j++) {
      const uint32_t gb = *reinterpret_cast<const uint32_t*>(g_mod + 5 * DM + n0 + 8 * j + 2 * t4);
      uint32_t p01 = bmul2(gb, pack_bf(acc[4 * j], acc[4 * j + 1]));
      uint32_t p23 = bmul2(gb, pack_bf(acc[4 * j + 2], acc[4 * j + 3]));
      *reinterpret_cast<uint32_t*>(stg + (16 * w4 + g8) * ROWB + (8 * j + 2 * t4) * 2) = p01;
      *reinterpret_cast<uint32_t*>(stg + (16 * w4 + g8 + 8) * ROWB + (8 * j + 2 * t4) * 2) = p23;
    }
    asm volatile("bar.sync 2, 128;" ::: "memory");
    TS(3, 4, tid == 0);
#pragma unroll
    for (int i = 0; i < 8; i++) {
      const int idx = t + 128 * i;
      const int r = idx >> 4, cv = idx & 15;
      uint4 v = *reinterpret_cast<const uint4*>(stg + r * ROWB + cv * 16);
      const uint4 xr = xpre[i];
      v.x = badd2(xr.x, v.x); v.y = badd2(xr.y, v.y); v.z = badd2(xr.z, v.z); v.w = badd2(xr.w, v.w);
      *reinterpret_cast<uint4*>(outp + (size_t)(m0 + r) * DM + n0 + cv * 8) = v;
    }
    TS(3, 5, tid == 0);
  }
}

typedef CUresult (*PFN_encodeTiled)(CUtensorMap*, CUtensorMapDataType, cuuint32_t, void*, const cuuint64_t*,
                                    const cuuint64_t*, const cuuint32_t*, const cuuint32_t*, CUtensorMapInterleave,
                                    CUtensorMapSwizzle, CUtensorMapL2promotion, CUtensorMapFloatOOBfill);

static void make_tmap(PFN_encodeTiled enc, CUtensorMap* tm, void* ptr, uint64_t inner, uint64_t outer,
                      uint32_t box_inner, uint32_t box_outer) {
  cuuint64_t gdim[2] = {inner, outer};
  cuuint64_t gstr[1] = {inner * 2};
  cuuint32_t box[2] = {box_inner, box_outer};
  cuuint32_t estr[2] = {1, 1};
  enc(tm, CU_TENSOR_MAP_DATA_TYPE_BFLOAT16, 2, ptr, gdim, gstr, box, estr, CU_TENSOR_MAP_INTERLEAVE_NONE,
      CU_TENSOR_MAP_SWIZZLE_128B, CU_TENSOR_MAP_L2_PROMOTION_L2_256B, CU_TENSOR_MAP_FLOAT_OOB_FILL_NONE);
}

constexpr int G1_BN = 256, G1_STAGES = 4, G1_CL = 1;

template <typename... KArgs, typename... Args>
static void launch_pdl(void (*kern)(KArgs...), dim3 grid, dim3 block, size_t smem, int cluster_x, Args... args) {
  cudaLaunchConfig_t cfg = {};
  cfg.gridDim = grid; cfg.blockDim = block; cfg.dynamicSmemBytes = smem; cfg.stream = cudaStreamPerThread;
  cudaLaunchAttribute at[2];
  at[0].id = cudaLaunchAttributeProgrammaticStreamSerialization;
  at[0].val.programmaticStreamSerializationAllowed = 1;
  at[1].id = cudaLaunchAttributeClusterDimension;
  at[1].val.clusterDim.x = cluster_x; at[1].val.clusterDim.y = 1; at[1].val.clusterDim.z = 1;
  cfg.attrs = at; cfg.numAttrs = cluster_x > 1 ? 2 : 1;
  cudaLaunchKernelEx(&cfg, kern, KArgs(args)...);
}

extern "C" void kernel_launch(void* const* d_in, const int* in_sizes, int n_in, void* d_out, int out_size) {
  const __nv_bfloat16* A_q = (const __nv_bfloat16*)d_in[0];
  const __nv_bfloat16* A_k = (const __nv_bfloat16*)d_in[1];
  const __nv_bfloat16* A_v = (const __nv_bfloat16*)d_in[2];
  const __nv_bfloat16* A_shift = (const __nv_bfloat16*)d_in[3];
  const __nv_bfloat16* A_ssmk = (const __nv_bfloat16*)d_in[4];
  const __nv_bfloat16* A_ssmD = (const __nv_bfloat16*)d_in[5];
  const __nv_bfloat16* B_w1 = (const __nv_bfloat16*)d_in[7];
  const __nv_bfloat16* B_w2 = (const __nv_bfloat16*)d_in[8];
  const __nv_bfloat16* cvec = (const __nv_bfloat16*)d_in[9];
  const __nv_bfloat16* w_mod = (const __nv_bfloat16*)d_in[10];

  CUtensorMap tmA1, tmB1, tmA2, tmB2;
  PFN_encodeTiled enc = nullptr;
  cudaDriverEntryPointQueryResult qr;
  cudaGetDriverEntryPoint("cuTensorMapEncodeTiled", (void**)&enc, cudaEnableDefault, &qr);
  void *ph2, *pH;
  cudaGetSymbolAddress(&ph2, g_h2);
  cudaGetSymbolAddress(&pH, g_H);
  make_tmap(enc, &tmA1, ph2, DM, S_LEN, 64, 128 / G1_CL);
  make_tmap(enc, &tmB1, (void*)B_w1, FF, DM, 64, 64);
  make_tmap(enc, &tmA2, pH, FF, S_LEN, 64, 64);
  make_tmap(enc, &tmB2, (void*)B_w2, DM, FF, 64, 64);
  const int G1_SMEM = G1_STAGES * (16384 + G1_BN * 128) + 128 * 176;
  cudaFuncSetAttribute(conv_kernel, cudaFuncAttributeMaxDynamicSharedMemorySize, K1_SMEM);
  cudaFuncSetAttribute(gemm_kernel<G1_BN, G1_STAGES, 0, G1_CL>, cudaFuncAttributeMaxDynamicSharedMemorySize, G1_SMEM);
  cudaFuncSetAttribute(gemm2_kernel, cudaFuncAttributeMaxDynamicSharedMemorySize, G2_SMEM);

  launch_pdl(kv_mod_kernel, dim3(128), dim3(256), 0, 1, A_k, A_v, A_shift, cvec, w_mod);
  launch_pdl(conv_kernel, dim3(128), dim3(K1_THREADS), K1_SMEM, 1, A_ssmk, A_ssmD);
  launch_pdl(ln_kernel, dim3(128), dim3(256), 0, 1, A_q);
  launch_pdl(gemm_kernel<G1_BN, G1_STAGES, 0, G1_CL>, dim3(FF / G1_BN, S_LEN / 128), dim3(384), G1_SMEM, G1_CL, tmA1, tmB1, DM,
             (__nv_bfloat16*)pH, FF, A_q);
  launch_pdl(gemm2_kernel, dim3(4, S_LEN / 64), dim3(256), G2_SMEM, 1, tmA2, tmB2, (__nv_bfloat16*)d_out);
}
```
